```python
import torch

def _softmax(x, axis=-1):
    return torch.softmax(x, dim=axis)
def _gelu(x):
    return torch.nn.functional.gelu(x, approximate="tanh")
def _silu(x):
    return torch.nn.functional.silu(x)
def _sigmoid(x):
    return torch.sigmoid(x)
def _layernorm(x, axis=-1, eps=1e-5):
    m = x.mean(dim=axis, keepdim=True)
    v = x.var(dim=axis, keepdim=True, unbiased=False)
    return (x - m) / torch.sqrt(v + eps)
def _scatter_add(tgt, idx, src, axis=0):
    return tgt.clone().index_add_(axis, idx, src)
def _segment_sum(src, seg, n):
    out = torch.zeros((n,) + src.shape[1:], dtype=src.dtype)
    return out.index_add_(0, seg, src)
def _pad(x, pw):
    flat = tuple(v for pair in reversed(pw) for v in pair)
    return torch.nn.functional.pad(x, flat)

kernel_name = 'standalone__paged_block_table_kv_pagedattention__sampling'

def setup_inputs():

    _w = (lambda a: (lambda t: t.to(torch.bfloat16) if t.is_floating_point() else t)(torch.as_tensor(a)))
    B, Hq, Hkv, Sq, Skv, D = 16, 32, 8, 32, 4096, 128
    bs = 16
    nbps = max(1, Skv // bs)
    num_phys = B * nbps + 4
    bt = torch.randperm(num_phys)[: B * nbps].reshape(B, nbps).to(torch.int64)
    cl = (nbps * bs - (torch.arange(1, B + 1, dtype=torch.int64) * 2654435761) % max(1, nbps * bs // 2)).to(torch.int64)
    return {
        "q": _w((lambda *s: torch.randn(*s, dtype=torch.bfloat16) * 0.8)(B, Hq, Sq, D)),
        "k_cache": _w((lambda *s: torch.randn(*s, dtype=torch.bfloat16) * 0.8)(num_phys, bs, Hkv, D)),
        "v_cache": _w((lambda *s: torch.randn(*s, dtype=torch.bfloat16) * 0.05)(num_phys, bs, Hkv, D)),
        "block_table": _w(bt),
        "context_lens": _w(cl),
    }

def reference(q, k_cache, v_cache, block_table, context_lens):
    B, Hq, Sq, D = q.shape
    bs = k_cache.shape[1]
    Hkv = k_cache.shape[2]
    nbps = block_table.shape[1]
    Skv = nbps * bs
    bt = block_table.reshape(-1)
    k = (lambda x, *d: x.permute(*d))(k_cache[bt].reshape(B, Skv, Hkv, D), 0, 2, 1, 3)
    v = (lambda x, *d: x.permute(*d))(v_cache[bt].reshape(B, Skv, Hkv, D), 0, 2, 1, 3)
    g = Hq // Hkv
    qg = q.reshape(B, Hkv, g, Sq, D)
    scores = torch.einsum("bhgqd,bhkd->bhgqk", qg, k) * (D ** -0.5)
    pos = torch.arange(Skv)
    msk = pos[None, :] < context_lens[:, None]
    scores = torch.where(msk[:, None, None, None, :], scores, -1e9)
    p = _softmax(scores, axis=-1)
    out = torch.einsum("bhgqk,bhkd->bhgqd", p, v)
    return out.reshape(B, Hq, Sq, D)
```

```cpp
#include <cuda_runtime.h>
#include <cuda_bf16.h>
#include <cuda.h>
#include <stdint.h>

namespace {

constexpr int kB = 16, kHkv = 8, kD = 128, kPage = 16, kMaxPages = 256;
constexpr int kRows = 128;
constexpr int kTilePages = 8;
constexpr int kSlotBytes = 32768, kPageBytes = 4096;
constexpr int kNumSlots = 7;
constexpr int kTailUnits = 16;
constexpr int kGrid = kB * kHkv;
constexpr int kThreads = 384;
constexpr int kAhead = 18;
constexpr int kTaper = 4, kTaperFrom = 64, kTaperTo = 32;
constexpr int kAheadStart = 6, kFade = 128;
constexpr int kEndPages = 64;
constexpr int kLead = 5;
constexpr int kTau = 4096;
constexpr int kHeadPages = 8;
constexpr int kShared = 3;
constexpr int kSendAfter = 4;
constexpr int kBitmapWords = 132;
constexpr uint32_t kUnit = 1u << 25;
static_assert((unsigned long long)kUnit * kGrid == (1ull << 32), "counter must wrap to zero after every launch");

constexpr int kOffRing = 0;
constexpr int kOffMisc = kOffRing + kNumSlots * kSlotBytes;
constexpr int kOffPages = kOffMisc;
constexpr int kOffBitmap = kOffPages + kMaxPages * 4;
constexpr int kOffCounts = kOffBitmap + kBitmapWords * 4;
constexpr int kOffBars = kOffCounts + 256;
constexpr int kOffFlags = kOffBars + (2 * kNumSlots + kTailUnits + 4) * 8;
constexpr int kFlagWords = 6;
constexpr int kSmemBytes = kOffFlags + kFlagWords * 4;
static_assert(kSmemBytes <= 232448 && kOffFlags % 16 == 0, "shared memory budget");

__device__ uint32_t g_progress;

__device__ __forceinline__ uint32_t smem_u32(const void* p) { return (uint32_t)__cvta_generic_to_shared(p); }
__device__ __forceinline__ void mbar_init(uint32_t bar, uint32_t cnt) {
    asm volatile("mbarrier.init.shared::cta.b64 [%0], %1;" ::"r"(bar), "r"(cnt) : "memory");
}
__device__ __forceinline__ void mbar_expect_tx(uint32_t bar, uint32_t bytes) {
    asm volatile("mbarrier.arrive.expect_tx.shared::cta.b64 _, [%0], %1;" ::"r"(bar), "r"(bytes) : "memory");
}
__device__ __forceinline__ void mbar_arrive(uint32_t bar) {
    asm volatile("mbarrier.arrive.shared::cta.b64 _, [%0];" ::"r"(bar) : "memory");
}
__device__ __forceinline__ void mbar_wait(uint32_t bar, uint32_t parity) {
    asm volatile(
        "{ .reg .pred p; .reg .u32 c;\n"
        "mov.u32 c, 0;\n"
        "WAIT_%=: mbarrier.try_wait.parity.shared::cta.b64 p, [%0], %1;\n"
        "@p bra.uni DONE_%=;\n"
        "add.u32 c, c, 1;\n"
        "setp.gt.u32 p, c, 0x1000000;\n"
        "@p trap;\n"
        "bra.uni WAIT_%=;\n"
        "DONE_%=: }"
        ::"r"(bar), "r"(parity) : "memory");
}
__device__ __forceinline__ uint32_t mbar_test(uint32_t bar, uint32_t parity) {
    uint32_t ok;
    asm volatile("{ .reg .pred p; mbarrier.test_wait.parity.shared::cta.b64 p, [%1], %2; selp.u32 %0, 1, 0, p; }"
                 : "=r"(ok) : "r"(bar), "r"(parity) : "memory");
    return ok;
}
__device__ __forceinline__ uint32_t clock_u32() {
    uint32_t c;
    asm volatile("mov.u32 %0, %%clock;" : "=r"(c));
    return c;
}
__device__ __forceinline__ uint32_t clock_after(uint32_t dep) {
    uint32_t c;
    asm volatile("{ .reg .pred p; setp.eq.u32 p, %1, 0xffffffff; mov.u32 %0, 0; @!p mov.u32 %0, %%clock; }" : "=r"(c) : "r"(dep));
    return c;
}
__device__ __forceinline__ void trap_if(bool c) {
    asm volatile("{ .reg .pred p; setp.ne.b32 p, %0, 0; @p trap; }" ::"r"((int)c));
}
__device__ __forceinline__ void sched_fence(float x) {
    asm volatile(
        "{ .reg .pred p; .reg .u32 t;\n"
        "setp.lt.f32 p, %0, 0f00000000;\n"
        "@!p bra D_%=;\n"
        "F_%=: mov.u32 t, %%clock;\n"
        "setp.eq.u32 p, t, 0;\n"
        "@p bra F_%=;\n"
        "D_%=: }" ::"f"(x) : "memory");
}
__device__ __forceinline__ uint32_t lds_volatile(uint32_t a) {
    uint32_t v;
    asm volatile("ld.volatile.shared.u32 %0, [%1];" : "=r"(v) : "r"(a) : "memory");
    return v;
}
__device__ __forceinline__ void sts_volatile(uint32_t a, uint32_t v) {
    asm volatile("st.volatile.shared.u32 [%0], %1;" ::"r"(a), "r"(v) : "memory");
}
__device__ __forceinline__ void tma_load_page(uint32_t dst, const CUtensorMap* map, uint32_t bar, int half, int row8, int head, uint64_t pol, int row = 0) {
    asm volatile(
        "cp.async.bulk.tensor.5d.shared::cluster.global.mbarrier::complete_tx::bytes.L2::cache_hint "
        "[%0], [%1, {%3, %8, %7, %4, %5}], [%2], %6;"
        ::"r"(dst), "l"(map), "r"(bar), "r"(0), "r"(row8), "r"(head), "l"(pol), "r"(half), "r"(row) : "memory");
}
__device__ __forceinline__ void tma_load_2d(uint32_t dst, const CUtensorMap* map, uint32_t bar, int c0, int c1) {
    asm volatile(
        "cp.async.bulk.tensor.2d.shared::cluster.global.mbarrier::complete_tx::bytes [%0], [%1, {%3, %4}], [%2];"
        ::"r"(dst), "l"(map), "r"(bar), "r"(c0), "r"(c1) : "memory");
}
__device__ __forceinline__ void tma_store_2d(const CUtensorMap* map, uint32_t src, int c0, int c1) {
    asm volatile("cp.async.bulk.tensor.2d.global.shared::cta.bulk_group [%0, {%2, %3}], [%1];"
                 ::"l"(map), "r"(src), "r"(c0), "r"(c1) : "memory");
}
__device__ __forceinline__ float ex2(float x) {
    float y;
    asm("ex2.approx.ftz.f32 %0, %1;" : "=f"(y) : "f"(x));
    return y;
}
__device__ __forceinline__ float rcp(float x) {
    float y;
    asm("rcp.approx.ftz.f32 %0, %1;" : "=f"(y) : "f"(x));
    return y;
}
__device__ __forceinline__ uint32_t pack_bf16(float lo, float hi) {
    uint32_t r;
    asm("cvt.rn.bf16x2.f32 %0, %1, %2;" : "=r"(r) : "f"(hi), "f"(lo));
    return r;
}
__device__ __forceinline__ uint32_t desc_lo(uint32_t addr, uint32_t lbo) { return ((addr & 0x3FFFF) >> 4) | ((lbo >> 4) << 16); }
constexpr uint32_t kDescHi = (2048 >> 4) | (1u << 30), kDescHiDense = (1024 >> 4) | (1u << 30);
__device__ __forceinline__ void wg_fence() { asm volatile("wgmma.fence.sync.aligned;" ::: "memory"); }
__device__ __forceinline__ void wg_commit() { asm volatile("wgmma.commit_group.sync.aligned;" ::: "memory"); }
template <int N> __device__ __forceinline__ void wg_wait() { asm volatile("wgmma.wait_group.sync.aligned %0;" ::"n"(N) : "memory"); }
template <int N> __device__ __forceinline__ void wg_wait_release(uint32_t bar, int lane) {
    asm volatile(
        "{ .reg .pred p; setp.eq.s32 p, %2, 0;\n"
        "wgmma.wait_group.sync.aligned %0;\n"
        "@p mbarrier.arrive.shared::cta.b64 _, [%1]; }" ::"n"(N), "r"(bar), "r"(lane) : "memory");
}
template <int N> __device__ __forceinline__ void pin(float (&r)[N]) {
#pragma unroll
    for (int i = 0; i < N; i++) asm volatile("" : "+f"(r[i])::"memory");
}
template <int N> __device__ __forceinline__ void pin(uint32_t (&r)[N]) {
#pragma unroll
    for (int i = 0; i < N; i++) asm volatile("" : "+r"(r[i])::"memory");
}

#define ACC_REGS                                                                        \
    "{%0, %1, %2, %3, %4, %5, %6, %7, %8, %9, %10, %11, %12, %13, %14, %15, "           \
    "%16, %17, %18, %19, %20, %21, %22, %23, %24, %25, %26, %27, %28, %29, %30, %31, "  \
    "%32, %33, %34, %35, %36, %37, %38, %39, %40, %41, %42, %43, %44, %45, %46, %47, "  \
    "%48, %49, %50, %51, %52, %53, %54, %55, %56, %57, %58, %59, %60, %61, %62, %63}"
#define ACC8(d, i) "+f"(d[i]), "+f"(d[i + 1]), "+f"(d[i + 2]), "+f"(d[i + 3]), "+f"(d[i + 4]), "+f"(d[i + 5]), "+f"(d[i + 6]), "+f"(d[i + 7])
#define ACC_OPS(d) ACC8(d, 0), ACC8(d, 8), ACC8(d, 16), ACC8(d, 24), ACC8(d, 32), ACC8(d, 40), ACC8(d, 48), ACC8(d, 56)

template <int kAcc, int kTrans> __device__ __forceinline__ void mma(float (&d)[64], const uint32_t* a, uint32_t db) {
    asm volatile(
        "{ .reg .b64 db; mov.b64 db, {%68, %69};\n"
        "wgmma.mma_async.sync.aligned.m64n128k16.f32.bf16.bf16 " ACC_REGS ", {%64, %65, %66, %67}, db, %70, 1, 1, %71; }"
        : ACC_OPS(d) : "r"(a[0]), "r"(a[1]), "r"(a[2]), "r"(a[3]), "r"(db), "n"(kDescHi), "n"(kAcc), "n"(kTrans));
}
#define HALF_MMA(acc)                                                                                             \
    "{ .reg .b64 db; mov.b64 db, {%36, %37};\n"                                                                   \
    "wgmma.mma_async.sync.aligned.m64n64k16.f32.bf16.bf16 "                                                       \
    "{%0, %1, %2, %3, %4, %5, %6, %7, %8, %9, %10, %11, %12, %13, %14, %15, "                                     \
    "%16, %17, %18, %19, %20, %21, %22, %23, %24, %25, %26, %27, %28, %29, %30, %31}, {%32, %33, %34, %35}, db, " \
    acc ", 1, 1, 1; }"
#define OUT8(d, i) "=f"(d[i]), "=f"(d[i + 1]), "=f"(d[i + 2]), "=f"(d[i + 3]), "=f"(d[i + 4]), "=f"(d[i + 5]), "=f"(d[i + 6]), "=f"(d[i + 7])
template <bool kAcc> __device__ __forceinline__ void mma_half(float (&d)[32], const uint32_t* a, uint32_t db) {
    if (kAcc)
        asm volatile(HALF_MMA("1") : ACC8(d, 0), ACC8(d, 8), ACC8(d, 16), ACC8(d, 24)
                     : "r"(a[0]), "r"(a[1]), "r"(a[2]), "r"(a[3]), "r"(db), "n"(kDescHiDense));
    else
        asm volatile(HALF_MMA("0") : OUT8(d, 0), OUT8(d, 8), OUT8(d, 16), OUT8(d, 24)
                     : "r"(a[0]), "r"(a[1]), "r"(a[2]), "r"(a[3]), "r"(db), "n"(kDescHiDense));
}
template <int J0, int J1, bool kFresh = false>
__device__ __forceinline__ void tail_units(float (&d)[32], const uint32_t (&p)[32], uint32_t db, uint32_t bars) {
#pragma unroll
    for (int j = J0; j < J1; j++) {
        mbar_wait(bars + 8 * j, 0);
        wg_fence();
        if (kFresh && j == 0) mma_half<false>(d, p + 8 * j, db + j * (kPageBytes >> 4));
        else mma_half<true>(d, p + 8 * j, db + j * (kPageBytes >> 4));
        mma_half<true>(d, p + 8 * j + 4, db + j * (kPageBytes >> 4) + (2048 >> 4));
        wg_commit();
    }
}
__device__ __forceinline__ void stsm4(uint32_t addr, uint32_t r0, uint32_t r1, uint32_t r2, uint32_t r3) {
    asm volatile("stmatrix.sync.aligned.m8n8.x4.shared.b16 [%0], {%1, %2, %3, %4};"
                 ::"r"(addr), "r"(r0), "r"(r1), "r"(r2), "r"(r3) : "memory");
}
__device__ __forceinline__ void scale_rows(float (&o)[64], float f0, float f1) {
#pragma unroll
    for (int j = 0; j < 16; j++) {
        o[4 * j] *= f0;
        o[4 * j + 1] *= f0;
        o[4 * j + 2] *= f1;
        o[4 * j + 3] *= f1;
    }
}
__device__ __forceinline__ void issue_qk(float (&s)[64], const uint32_t (&qf)[32], uint32_t dk) {
    mma<0, 0>(s, qf, dk);
#pragma unroll
    for (int k = 1; k < 8; k++) mma<1, 0>(s, qf + 4 * k, dk + (((k >> 2) * 1024 + (k & 3) * 32) >> 4));
}
__device__ __forceinline__ void issue_pv(float (&o)[64], const uint32_t (&p)[32], uint32_t dv) {
#pragma unroll
    for (int k = 0; k < 8; k++) mma<1, 1>(o, p + 4 * k, dv + k * (kPageBytes >> 4));
}

__device__ __forceinline__ void item_of(int i, int nt, int& tile, int& is_v) {
    if (nt >= 3 && (i >> 1) == nt - 2) i ^= 1;
    is_v = (i != 0) & ~i & 1;
    tile = is_v ? (i >> 1) - 1 : (i + 1) >> 1;
}

struct Pace {
    int knee, total;
    uint32_t step, end_step;
    __device__ __forceinline__ Pace(int np, int all_pages) {
        total = 2 * np;
        end_step = (uint32_t)((float)kUnit * ((float)kB / (float)(2 * all_pages)));
        const bool bend = total > 2 * kEndPages && all_pages * 2 > 2 * kEndPages * kB;
        knee = bend ? total - kEndPages : total;
        step = (kUnit - (uint32_t)(total - knee) * end_step) / (uint32_t)knee;
    }
    __device__ __forceinline__ uint32_t at(int c) const {
        return c < knee ? (uint32_t)c * step : kUnit - (uint32_t)(total - c) * end_step;
    }
};

struct Seq {
    bool flat;
    int cl, np, nt;
    int first_pages;
    int nitems;
    int quads;
    bool trim;
    __device__ __forceinline__ explicit Seq(int len) {
        flat = len <= 0;
        cl = flat ? kMaxPages * kPage : min(len, kMaxPages * kPage);
        np = (cl + kPage - 1) >> 4;
        nt = (np + kTilePages - 1) >> 3;
        first_pages = np - (nt - 1) * kTilePages;
        nitems = max(2 * nt, 3);
        quads = (cl - (np - 1) * kPage + 3) >> 2;
        trim = nt >= 4;
    }
};

struct Ring {
    int slot = 0;
    uint32_t phase = 0;
    __device__ __forceinline__ void next() {
        if (++slot == kNumSlots) { slot = 0; phase ^= 1; }
    }
};

template <bool kFirst>
__device__ __forceinline__ void softmax_tile(float (&s)[64], float (&m)[2], float (&l)[2], float (&a)[2], int ncols, int lane) {
    constexpr float c = 0.08838834764831845f * 1.4426950408889634f;
    if (kFirst) {
        const int lim = ncols - 2 * (lane & 3);
#pragma unroll
        for (int i = 0; i < 64; i++) s[i] = (8 * (i >> 2) + (i & 1) < lim) ? s[i] : -INFINITY;
    }
    float mq[2][4];
#pragma unroll
    for (int g = 0; g < 4; g++) {
#pragma unroll
        for (int e = 0; e < 2; e++) {
            mq[e][g] = fmaxf(s[4 * g + 2 * e], s[4 * g + 2 * e + 1]);
#pragma unroll
            for (int j = g + 4; j < 16; j += 4) mq[e][g] = fmaxf(fmaxf(mq[e][g], s[4 * j + 2 * e]), s[4 * j + 2 * e + 1]);
        }
    }
    float mx0 = fmaxf(fmaxf(mq[0][0], mq[0][1]), fmaxf(mq[0][2], mq[0][3]));
    float mx1 = fmaxf(fmaxf(mq[1][0], mq[1][1]), fmaxf(mq[1][2], mq[1][3]));
    mx0 = fmaxf(mx0, __shfl_xor_sync(0xffffffffu, mx0, 1));
    mx1 = fmaxf(mx1, __shfl_xor_sync(0xffffffffu, mx1, 1));
    mx0 = fmaxf(mx0, __shfl_xor_sync(0xffffffffu, mx0, 2));
    mx1 = fmaxf(mx1, __shfl_xor_sync(0xffffffffu, mx1, 2));
    if (!kFirst) {
        mx0 = fmaxf(mx0, m[0]);
        mx1 = fmaxf(mx1, m[1]);
    }
    const float b0 = __fmul_rn(mx0, -c), b1 = __fmul_rn(mx1, -c);
    if (!kFirst) {
        a[0] = ex2(__fadd_rn(__fmul_rn(m[0], c), b0));
        a[1] = ex2(__fadd_rn(__fmul_rn(m[1], c), b1));
    }
    m[0] = mx0;
    m[1] = mx1;
    float r0 = 0.f, r1 = 0.f;
#pragma unroll
    for (int j = 0; j < 16; j++) {
        s[4 * j] = ex2(fmaf(s[4 * j], c, b0));
        s[4 * j + 1] = ex2(fmaf(s[4 * j + 1], c, b0));
        s[4 * j + 2] = ex2(fmaf(s[4 * j + 2], c, b1));
        s[4 * j + 3] = ex2(fmaf(s[4 * j + 3], c, b1));
        r0 += s[4 * j] + s[4 * j + 1];
        r1 += s[4 * j + 2] + s[4 * j + 3];
    }
    if (kFirst) { l[0] = r0; l[1] = r1; }
    else { l[0] = fmaf(l[0], a[0], r0); l[1] = fmaf(l[1], a[1], r1); }
}

__global__ void __launch_bounds__(kThreads, 1)
paged_attn_kernel(const __nv_bfloat16* __restrict__ q, const int* __restrict__ block_table, const int* __restrict__ context_lens,
                  __nv_bfloat16* __restrict__ out, int num_phys,
                  const __grid_constant__ CUtensorMap map_q, const __grid_constant__ CUtensorMap map_k,
                  const __grid_constant__ CUtensorMap map_v, const __grid_constant__ CUtensorMap map_vh,
                  const __grid_constant__ CUtensorMap map_o, const __grid_constant__ CUtensorMap map_k4,
                  const __grid_constant__ CUtensorMap map_v4) {
    extern __shared__ __align__(1024) unsigned char sptr[];
    const uint32_t sbase = smem_u32(sptr);
    const uint32_t bar_full = sbase + kOffBars, bar_empty = bar_full + 8 * kNumSlots, bar_tail = bar_empty + 8 * kNumSlots;
    const uint32_t bar_q = bar_tail + 8 * kTailUnits, bar_qfree = bar_q + 8, bar_staged = bar_qfree + 8;
    const uint32_t s_q = sbase + kOffRing + (kNumSlots - 1) * kSlotBytes;
    const uint32_t s_prog = sbase + kOffFlags, s_rate = s_prog + 8, s_done = s_prog + 12, s_stop = s_prog + 16, s_zero = s_prog + 20;
    int* s_pages = reinterpret_cast<int*>(sptr + kOffPages);
    uint32_t* s_bitmap = reinterpret_cast<uint32_t*>(sptr + kOffBitmap);

    const int tid = threadIdx.x, lane = tid & 31;
    const int bh = blockIdx.x, b = bh >> 3, h = bh & 7;

    int cl_lane, my_page = 0;
    if (tid < 256) {
        asm volatile("ld.global.nc.s32 %0, [%1];" : "=r"(my_page) : "l"(block_table + (uint32_t)(b * kMaxPages + tid)));
        asm volatile("ld.global.nc.s32 %0, [%1];" : "=r"(cl_lane) : "l"(context_lens + b));
    } else {
        asm volatile(
            "{ .reg .pred p; .reg .u32 t;\n"
            "setp.ne.u32 p, %2, 320;\n"
            "@p bra S_%=;\n"
            "cp.async.bulk.prefetch.L2.global [%0], %1;\n"
            "F_%=: mov.u32 t, %%clock;\n"
            "setp.eq.u32 p, t, 0;\n"
            "@p bra F_%=;\n"
            "S_%=: }" ::"l"(q + (size_t)bh * kRows * kD), "r"(32768), "r"(tid) : "memory");
        asm volatile("ld.global.nc.s32 %0, [%1];" : "=r"(cl_lane) : "l"(context_lens + (lane & (kB - 1))));
    }
    const int warp = __shfl_sync(0xffffffffu, tid >> 5, 0);
    uint64_t pol;
    asm("createpolicy.fractional.L2::evict_first.b64 %0, 1.0;" : "=l"(pol));

    if (warp == 8) {
        if (lane == 0) {
            mbar_init(bar_q, 1);
            asm volatile("fence.mbarrier_init.release.cluster;" ::: "memory");
            mbar_expect_tx(bar_q, 32768);
            tma_load_2d(s_q, &map_q, bar_q, 0, bh * kRows);
            tma_load_2d(s_q + 16384, &map_q, bar_q, 64, bh * kRows);
        }
    } else if (warp == 9) {
        if (lane == 0) {
            for (int i = 0; i < kNumSlots; i++) mbar_init(bar_full + 8 * i, 1);
            asm volatile("fence.mbarrier_init.release.cluster;" ::: "memory");
        }
    } else if (warp == 10) {
        if (lane == 0) {
            asm volatile("prefetch.tensormap [%0];" ::"l"(&map_k) : "memory");
            asm volatile("prefetch.tensormap [%0];" ::"l"(&map_v) : "memory");
            asm volatile("prefetch.tensormap [%0];" ::"l"(&map_k4) : "memory");
            asm volatile("prefetch.tensormap [%0];" ::"l"(&map_v4) : "memory");
        }
    } else if (warp == 11) {
        trap_if(sbase & 1023);
        if (lane < kFlagWords) sts_volatile(s_prog + 4 * lane, 0);
        if (lane == 0) {
            for (int i = 0; i < kNumSlots; i++) mbar_init(bar_empty + 8 * i, 9);
            mbar_init(bar_qfree, 8);
            mbar_init(bar_staged, 4);
            mbar_init(bar_staged + 8, 4);
        }
    } else if (tid < kBitmapWords) {
        s_bitmap[tid] = 0;
    }
    __syncthreads();
    if (warp == 9) {
        if (lane == 0) {
            for (int i = 0; i < kTailUnits; i++) mbar_init(bar_tail + 8 * i, 1);
            for (int i = 0; i < kTailUnits; i++) mbar_expect_tx(bar_tail + 8 * i, kPageBytes);
            asm volatile("fence.mbarrier_init.release.cluster;" ::: "memory");
        }
        __syncwarp();
        asm volatile("bar.arrive 2, 320;" ::: "memory");
        asm volatile("bar.arrive 7, 320;" ::: "memory");
    }

    if (warp >= 8) {
        asm volatile("setmaxnreg.dec.sync.aligned.u32 40;");
        const Seq sq(__shfl_sync(0xffffffffu, cl_lane, b + lds_volatile(s_zero)));
        const bool flat = sq.flat, side_fill = sq.trim, by_quads = sq.trim && sq.quads < 4;
        const int np = sq.np, nt = sq.nt, first_pages = sq.first_pages, nitems = sq.nitems, quads = sq.quads;
        const uint32_t tail_pages = nt >= 3 ? 0xffffu : nt == 2 ? 0xff00u | ((1u << first_pages) - 1) : ((1u << first_pages) - 1) << 8;
        const int head = sq.trim && !flat ? kHeadPages : 0;
        if (warp == 11) {
            const int slot = lane >= first_pages;
            const uint32_t dst0 = sbase + kOffRing + slot * kSlotBytes + (lane - slot * first_pages) * kPageBytes;
            uint32_t first = lane < head && !(by_quads && lane == first_pages - 1), dst_r = dst0, full_r = bar_full + 8 * slot;
            asm volatile("" : "+r"(first), "+r"(dst_r), "+r"(full_r));
            asm volatile("bar.sync 7, 320;" ::: "memory");
            if (first) tma_load_page(dst_r, &map_k, full_r, 0, s_pages[lane] * 2, h, pol);
            const int qd = lane >> 1, hf = lane & 1;
            const int page = s_pages[first_pages - 1];
            const uint32_t dst = sbase + kOffRing + (first_pages - 1) * kPageBytes + (qd >> 1) * 2048 + hf * 1024 + (qd & 1) * 512;
            if (by_quads && qd < quads) {
                tma_load_page(dst, &map_k4, bar_full, hf, page * 2 + (qd >> 1), h, pol, (qd & 1) * 4);
                tma_load_page(dst + 2 * kSlotBytes, &map_v4, bar_full + 16, hf, page * 2 + (qd >> 1), h, pol, (qd & 1) * 4);
            }
        }
        const int c_lane = (cl_lane <= 0) ? kMaxPages * kPage : min(cl_lane, kMaxPages * kPage);
        const int all_pages = __reduce_add_sync(0xffffffffu, (lane < kB) ? (c_lane + kPage - 1) / kPage : 0);
        const Pace pace(np, all_pages);
        if (warp == 8 || warp == 11) {
            const uint32_t ahead = (uint32_t)fminf((float)kAhead * (float)pace.end_step, (float)kUnit);
            const uint32_t taper_step = ahead / (kAhead * (kTaperFrom - kTaperTo)) * kTaper;
            const int v0_item = nt == 3 ? 3 : 2;
            Ring r;
            r.slot = warp == 8 ? 0 : kShared;
            for (int i = r.slot; i < nitems; i += (i < kShared - 1) ? 1 : 2) {
                int issued = 8 * i - (i > 0 ? 8 - first_pages : 0) - (nt >= 3 && i > v0_item ? 8 - first_pages : 0);
                if (i == nitems - 1) issued += (min(np, 16) >> 1) - 8;
                const bool tail = i >= nitems - 2;
                const int half = tail ? i - (nitems - 2) : 0;
                int tile, is_v, n, idx;
                bool pending, real;
                item_of(i, nt, tile, is_v);
                if (tail) {
                    n = (min(np, 16) + half) >> 1;
                    idx = nt >= 2 ? (nt == 2 && lane < 8 ? lane : np - 16 + lane) : lane - 8;
                    pending = lane < 16;
                    real = lane < 16 && (tail_pages >> lane & 1);
                } else {
                    n = tile ? kTilePages : first_pages;
                    idx = (tile ? first_pages + (tile - 1) * kTilePages : 0) + lane;
                    pending = lane < (is_v && !side_fill ? kTilePages : n) && !(by_quads && tile == 0 && lane == n - 1) &&
                              !(i < 2 && idx < head);
                    real = lane < n && (is_v || !flat);
                }
                const uint32_t full = tail ? bar_tail + 8 * (8 * half + (lane >> 1)) : bar_full + 8 * r.slot;
                if (i == kNumSlots - 1) mbar_wait(bar_qfree, 0);
                if (i == nitems - 3) {
                    asm volatile("prefetch.tensormap [%0];" ::"l"(&map_vh) : "memory");
                    asm volatile("prefetch.tensormap [%0];" ::"l"(&map_o) : "memory");
                }
                mbar_wait(bar_empty + 8 * r.slot, r.phase ^ 1);
                if (!tail && lane == 0)
                    mbar_expect_tx(full, is_v && !side_fill ? kSlotBytes : n * kPageBytes - (by_quads && tile == 0 ? (4 - quads) * 1024 : 0));
                __syncwarp();
                const uint32_t dst = sbase + kOffRing + r.slot * kSlotBytes + lane * (tail ? kPageBytes / 2 : kPageBytes);
                const CUtensorMap* map = tail ? &map_vh : is_v ? &map_v : &map_k;
                const int mine = issued + min((tail ? lane >> 1 : lane) + 1, n);
                const uint32_t boost = (uint32_t)max(kFade - mine, 0) * (pace.end_step / kFade * kAheadStart);
                const uint32_t taper = (uint32_t)min(max(kTaperFrom - (pace.total - mine), 0), kTaperFrom - kTaperTo) * taper_step;
                uint32_t need = pace.at(mine), room = ahead + boost - taper, dst_r = dst, full_r = full;
                asm volatile("" : "+r"(need), "+r"(room), "+r"(dst_r), "+r"(full_r), "+r"(idx));
                if (i == 0) asm volatile("bar.sync 2, 320;" ::: "memory");
                const int page = real ? s_pages[idx] : num_phys;
                uint32_t it = 0;
                do {
                    uint32_t prog, t_prog, rate, done;
                    asm volatile("ld.volatile.shared.v4.u32 {%0, %1, %2, %3}, [%4];"
                                 : "=r"(prog), "=r"(t_prog), "=r"(rate), "=r"(done) : "r"(s_prog) : "memory");
                    prog += rate * (uint32_t)min(max((int)(clock_u32() - t_prog), 0), 2048);
                    if (pending && (need <= prog + room || mine - (int)done <= kTilePages)) {
                        tma_load_page(dst_r, map, full_r, half, page * 2, h, pol);
                        pending = false;
                    }
                    trap_if(++it > (1u << 26));
                } while (__any_sync(0xffffffffu, pending));
                if (i >= kShared - 1) r.next();
                r.next();
            }
            const bool issued_last = (nitems - 1 < kShared || ((nitems - 1 - kShared) & 1)) == (warp == 8);
            if (lane == 0 && issued_last) sts_volatile(s_stop, 1);
            if (lane == 0 && !issued_last) {
                const uint32_t stage = sbase + kOffRing + (nitems % kNumSlots) * kSlotBytes;
                mbar_wait(bar_tail + 8 * (8 + kSendAfter), 0);
                uint32_t todo = 3, it = 0;
                while (todo) {
                    for (int g = 0; g < 2; g++) {
                        if ((todo >> g & 1) && mbar_test(bar_staged + 8 * g, 0)) {
                            tma_store_2d(&map_o, stage + g * 8192, 0, bh * kRows + g * 64);
                            todo &= ~(1u << g);
                        }
                    }
                    trap_if(++it > (1u << 26));
                }
                asm volatile("cp.async.bulk.commit_group;" ::: "memory");
                asm volatile("cp.async.bulk.wait_group.read 0;" ::: "memory");
            }
        } else if (warp == 9) {
            int done = 0;
            auto report = [&](int n) {
                const uint32_t inc = pace.at(done + n) - pace.at(done);
                done += n;
                if (lane == 0) {
                    sts_volatile(s_done, done);
                    asm volatile("red.relaxed.gpu.global.add.u32 [%0], %1;" ::"l"(&g_progress), "r"(inc) : "memory");
                }
            };
            Ring r;
            for (int i = 0; i < nitems - 2; i++) {
                int tile, is_v;
                item_of(i, nt, tile, is_v);
                mbar_wait(bar_full + 8 * r.slot, r.phase);
                if (lane == 0) mbar_arrive(bar_empty + 8 * r.slot);
                report(tile ? kTilePages : first_pages);
                r.next();
            }
            for (int i = 0; i < kTailUnits / 2; i++) mbar_wait(bar_tail + 8 * i, 0);
            report(min(np, 16) >> 1);
            mbar_wait(bar_tail + 8 * (kTailUnits / 2), 0);
            report(pace.total - done);
        } else if (warp == 10) {
            if (lane == 0) {
                uint32_t it = 0, prev = 0, t_prev = clock_u32(), t_ref = t_prev;
                float f_ref = 0.f, g = 0.f;
                const float lead = (float)kLead * (float)pace.end_step;
                while (!lds_volatile(s_stop)) {
                    uint32_t f;
                    asm volatile("ld.relaxed.gpu.global.u32 %0, [%1];" : "=r"(f) : "l"(&g_progress) : "memory");
                    f >>= 7;
                    uint32_t est = f + (f - min(prev, f));
                    prev = f;
                    const uint32_t t = clock_after(f);
                    const float ff = (float)f, dt = (float)(t - t_prev);
                    t_prev = t;
                    if (f < kUnit / 32) {
                        f_ref = ff;
                        t_ref = t;
                    }
                    if (f < kUnit / 10) {
                        g = (float)est;
                    } else {
                        const float rate = __fdividef(ff - f_ref, (float)(t - t_ref));
                        const float adv = rate * dt;
                        const float target = ff + 0.5f * adv;
                        sts_volatile(s_rate, (uint32_t)fminf(rate, 65536.f));
                        g += adv;
                        g += (target - g) * fminf(dt * (1.f / kTau), 1.f);
                        g = fminf(g, target + lead);
                        est = (uint32_t)g;
                    }
                    asm volatile("st.volatile.shared.v2.u32 [%0], {%1, %2};" ::"r"(s_prog), "r"(est), "r"(t) : "memory");
                    trap_if(++it > (1u << 22));
                }
            }
        }
    } else {
        const int len = cl_lane + (int)lds_volatile(s_zero);
        const uint32_t w = min((uint32_t)my_page >> 5, (uint32_t)kBitmapWords - 1), bit = 1u << (my_page & 31);
        const uint32_t in_sort = tid < kMaxPages - 1 && (len <= 0 || (tid + 1) * kPage < len);
        uint32_t seen, dup;
        asm volatile("{ .reg .pred p; setp.ne.u32 p, %3, 0; mov.u32 %0, 0; @p atom.shared.or.b32 %0, [%1], %2; }"
                     : "=&r"(seen) : "r"(sbase + kOffBitmap + 4 * w), "r"(bit), "r"(in_sort) : "memory");
        asm volatile("{ .reg .pred p, q; setp.ne.u32 p, %1, 0; bar.red.or.pred q, 1, 256, p; selp.u32 %0, 1, 0, q; }"
                     : "=r"(dup) : "r"((seen & bit) | (uint32_t)(num_phys > kBitmapWords * 32)) : "memory");
        const uint32_t grp = w >> 2, sub = w & 3;
        const uint4 va = reinterpret_cast<const uint4*>(s_bitmap)[lane];
        const uint4 vb = reinterpret_cast<const uint4*>(s_bitmap)[grp];
        int incl = __popc(va.x) + __popc(va.y) + __popc(va.z) + __popc(va.w);
        const uint32_t s_cnt = sbase + kOffCounts + warp * 32;
        asm volatile("st.shared.u8 [%0], %1;" ::"r"(s_cnt + lane), "r"(incl) : "memory");
        __syncwarp();
        uint32_t cw[8];
        asm volatile("ld.shared.v4.u32 {%0, %1, %2, %3}, [%4];" : "=r"(cw[0]), "=r"(cw[1]), "=r"(cw[2]), "=r"(cw[3]) : "r"(s_cnt) : "memory");
        asm volatile("ld.shared.v4.u32 {%0, %1, %2, %3}, [%4];" : "=r"(cw[4]), "=r"(cw[5]), "=r"(cw[6]), "=r"(cw[7]) : "r"(s_cnt + 16) : "memory");
        uint32_t acc0 = 0, acc1 = 0;
#pragma unroll
        for (int k = 0; k < 4; k++) {
            acc0 = __dp4a(cw[k], __funnelshift_rc(0x01010101u, 0u, max(8 * (4 * k + 4 - (int)grp), 0)), acc0);
            acc1 = __dp4a(cw[k + 4], __funnelshift_rc(0x01010101u, 0u, max(8 * (4 * k + 20 - (int)grp), 0)), acc1);
        }
        const int below = acc0 + acc1;
        const int rank = below + __popc(vb.x & (sub > 0 ? ~0u : bit - 1)) +
                         __popc(vb.y & (sub > 1 ? ~0u : sub == 1 ? bit - 1 : 0u)) +
                         __popc(vb.z & (sub > 2 ? ~0u : sub == 2 ? bit - 1 : 0u)) + __popc(vb.w & (sub == 3 ? bit - 1 : 0u));
        const Seq sq(__shfl_sync(0xffffffffu, len, 0));
        const bool flat = sq.flat, side_fill = sq.trim;
        const int cl = sq.cl, np = sq.np, nt = sq.nt, first_pages = sq.first_pages, nitems = sq.nitems, quads = sq.quads;
        int pos = dup ? tid : rank;
        if (tid == np - 1) pos = first_pages - 1;
        else if (pos >= first_pages - 1) pos++;
        if (tid < np) s_pages[pos] = my_page;
        asm volatile("bar.arrive 7, 320;" ::: "memory");
        asm volatile("bar.arrive 2, 320;" ::: "memory");
        asm volatile("setmaxnreg.inc.sync.aligned.u32 232;");

        const int wg = warp >> 2;
        const int first_cols = cl - (nt - 1) * kTilePages * kPage;
        const uint32_t dk0 = desc_lo(sbase + kOffRing, 16), dv0 = desc_lo(sbase + kOffRing, 1024);

        float o[64], s[64], m[2], l[2], a[2];
        uint32_t p[32], qf[32];
        Ring r;

        if (side_fill) {
            uint4* v0 = reinterpret_cast<uint4*>(sptr + kOffRing + 2 * kSlotBytes);
            const int quad_of_tid = (tid >> 7) * 2 + ((tid >> 5) & 1);
            if (quad_of_tid >= quads) v0[(first_pages - 1) * 256 + tid] = make_uint4(0, 0, 0, 0);
            for (int pg = first_pages; pg < kTilePages; pg++) v0[pg * 256 + tid] = make_uint4(0, 0, 0, 0);
            asm volatile("fence.proxy.async.shared::cta;" ::: "memory");
        }
        mbar_wait(bar_q, 0);
        {
            const uint32_t qrow = s_q + (warp * 16 + (lane & 15)) * 128;
#pragma unroll
            for (int k = 0; k < 8; k++) {
                const uint32_t addr = qrow + (k >> 2) * 16384 + ((((k & 3) * 2 + (lane >> 4)) ^ (lane & 7)) << 4);
                asm volatile("ldmatrix.sync.aligned.m8n8.x4.shared.b16 {%0, %1, %2, %3}, [%4];"
                             : "=r"(qf[4 * k]), "=r"(qf[4 * k + 1]), "=r"(qf[4 * k + 2]), "=r"(qf[4 * k + 3]) : "r"(addr) : "memory");
            }
            if (flat) {
#pragma unroll
                for (int i = 0; i < 32; i++) qf[i] = 0u;
            }
        }
        pin(qf);
        __syncwarp();
        if (lane == 0) mbar_arrive(bar_qfree);
        mbar_wait(bar_full + 8 * r.slot, r.phase);
        wg_fence();
        issue_qk(s, qf, dk0 + r.slot * (kSlotBytes >> 4));
        wg_commit();
        wg_wait<0>();
        pin(s);
        if (lane == 0) mbar_arrive(bar_empty + 8 * r.slot);
        r.next();
        softmax_tile<true>(s, m, l, a, first_cols, lane);
#pragma unroll
        for (int i = 0; i < 32; i++) p[i] = pack_bf16(s[2 * i], s[2 * i + 1]);
#pragma unroll
        for (int i = 0; i < 64; i++) o[i] = 0.f;
        const bool deep = nt >= 3;
        const int spare = nitems % kNumSlots;
        const uint32_t spare_free = ((nitems / kNumSlots) & 1) ^ 1;
        const uint32_t stage = sbase + kOffRing + spare * kSlotBytes + warp * 2048;
        float a_parked[2] = {1.f, 1.f};
        auto wg_count = [&](bool flag) {
            uint32_t n;
            if (wg == 0)
                asm volatile("{ .reg .pred p; setp.ne.u32 p, %1, 0; bar.red.popc.u32 %0, 3, 128, p; }" : "=r"(n) : "r"((uint32_t)flag) : "memory");
            else
                asm volatile("{ .reg .pred p; setp.ne.u32 p, %1, 0; bar.red.popc.u32 %0, 4, 128, p; }" : "=r"(n) : "r"((uint32_t)flag) : "memory");
            return (int)__shfl_sync(0xffffffffu, n, 0);
        };
        if (wg == 1 && nt > 1) asm volatile("bar.arrive 5, 256;" ::: "memory");

        auto start_scores = [&]() {
            const int ks = r.slot;
            mbar_wait(bar_full + 8 * ks, r.phase);
            r.next();
            if (wg == 0) asm volatile("bar.sync 5, 256;" ::: "memory");
            else asm volatile("bar.sync 6, 256;" ::: "memory");
            pin(o);
            pin(p);
            wg_fence();
            issue_qk(s, qf, dk0 + ks * (kSlotBytes >> 4));
            wg_commit();
            return ks;
        };
        auto pass_turn = [&]() {
            if (wg == 0) asm volatile("bar.arrive 6, 256;" ::: "memory");
            else asm volatile("bar.arrive 5, 256;" ::: "memory");
        };

        for (int t = 1; t < nt - 2; t++) {
            const int ks = start_scores();
            const int vs = r.slot;
            mbar_wait(bar_full + 8 * vs, r.phase);
            r.next();
            wg_fence();
            issue_pv(o, p, dv0 + vs * (kSlotBytes >> 4));
            wg_commit();
            pass_turn();
            wg_wait_release<1>(bar_empty + 8 * ks, lane);
            pin(s);
            softmax_tile<false>(s, m, l, a, 0, lane);
            pin(s);
            sched_fence(l[0] + l[1]);
            wg_wait_release<0>(bar_empty + 8 * vs, lane);
            pin(o);
            pin(p);
            if (__any_sync(0xffffffffu, a[0] != 1.f || a[1] != 1.f)) scale_rows(o, a[0], a[1]);
#pragma unroll
            for (int i = 0; i < 32; i++) p[i] = pack_bf16(s[2 * i], s[2 * i + 1]);
        }
        if (deep) {
            start_scores();
            pass_turn();
            mbar_wait(bar_empty + 8 * spare, spare_free);
            wg_wait<0>();
            pin(s);
            softmax_tile<false>(s, m, l, a_parked, 0, lane);
#pragma unroll
            for (int i = 0; i < 8; i++)
                asm volatile("st.shared.v4.u32 [%0], {%1, %2, %3, %4};"
                             ::"r"(stage + (i >> 2) * 16384 + (i & 3) * 512 + lane * 16),
                               "r"(pack_bf16(s[8 * i], s[8 * i + 1])), "r"(pack_bf16(s[8 * i + 2], s[8 * i + 3])),
                               "r"(pack_bf16(s[8 * i + 4], s[8 * i + 5])), "r"(pack_bf16(s[8 * i + 6], s[8 * i + 7])) : "memory");
        }
        a[0] = a[1] = 1.f;
        if (nt > 1) {
            start_scores();
            const uint32_t v_full = bar_full + 8 * r.slot, v_phase = r.phase, dv = dv0 + r.slot * (kSlotBytes >> 4);
            if (deep) r.next();
            const bool early = deep && wg_count(mbar_test(v_full, v_phase)) == 128;
            if (early) {
                wg_fence();
                issue_pv(o, p, dv);
                wg_commit();
                if (wg == 0) asm volatile("bar.arrive 6, 256;" ::: "memory");
                wg_wait<1>();
            } else {
                if (wg == 0) asm volatile("bar.arrive 6, 256;" ::: "memory");
                wg_wait<0>();
            }
            pin(s);
            pin(qf);
            softmax_tile<false>(s, m, l, a, 0, lane);
#pragma unroll
            for (int i = 0; i < 32; i++) qf[i] = pack_bf16(s[2 * i], s[2 * i + 1]);
            pin(qf);
            if (deep && !early) {
                mbar_wait(v_full, v_phase);
                wg_fence();
                issue_pv(o, p, dv);
                wg_commit();
            }
        } else {
#pragma unroll
            for (int i = 0; i < 32; i++) qf[i] = p[i];
        }

        l[0] += __shfl_xor_sync(0xffffffffu, l[0], 1);
        l[1] += __shfl_xor_sync(0xffffffffu, l[1], 1);
        l[0] += __shfl_xor_sync(0xffffffffu, l[0], 2);
        l[1] += __shfl_xor_sync(0xffffffffu, l[1], 2);
        const float inv0 = rcp(l[0]), inv1 = rcp(l[1]);
        const float fa0 = a[0] * inv0, fa1 = a[1] * inv1;
        const int mi = lane >> 3;
        uint32_t st_addr[4], ld_addr[2];
#pragma unroll
        for (int j = 0; j < 4; j++) st_addr[j] = stage + (lane & 15) * 128 + (((2 * j + (lane >> 4)) ^ (lane & 7)) << 4);
#pragma unroll
        for (int j = 0; j < 2; j++) ld_addr[j] = stage + 16384 + (4 * j + mi) * 128 + (((lane & 7) ^ (4 * j + mi)) << 4);
        uint4* dst = reinterpret_cast<uint4*>(out) + (size_t)(bh * kRows + warp * 16 + mi) * 16 + 8 + (lane & 7);
        pin(st_addr);
        pin(ld_addr);
        asm volatile("" : "+l"(dst));
        const uint32_t dv_lo = dv0 + r.slot * (kSlotBytes >> 4);
        r.next();
        const uint32_t dv_hi = dv0 + r.slot * (kSlotBytes >> 4);
        sched_fence(inv0 + inv1);
        wg_wait<0>();
        pin(o);
        pin(p);
        if (deep) {
#pragma unroll
            for (int i = 0; i < 8; i++)
                asm volatile("ld.shared.v4.u32 {%0, %1, %2, %3}, [%4];"
                             : "=r"(p[4 * i]), "=r"(p[4 * i + 1]), "=r"(p[4 * i + 2]), "=r"(p[4 * i + 3])
                             : "r"(stage + (i >> 2) * 16384 + (i & 3) * 512 + lane * 16) : "memory");
        } else {
            mbar_wait(bar_empty + 8 * spare, spare_free);
        }
        float lo[32], hi[32], x[32], y[32];
#pragma unroll
        for (int i = 0; i < 32; i++) lo[i] = o[i] * a_parked[(i >> 1) & 1];
        pin(lo);
        pin(p);
        tail_units<0, 2>(lo, p, dv_lo, bar_tail);
#pragma unroll
        for (int i = 0; i < 32; i++) hi[i] = o[32 + i] * a_parked[(i >> 1) & 1];
        pin(hi);
        tail_units<2, 4>(lo, p, dv_lo, bar_tail);
        tail_units<0, 4, true>(x, qf, dv_lo + (16384 >> 4), bar_tail + 32);
        auto stage_half = [&](const float (&u)[32], const float (&v)[32], const int half) {
#pragma unroll
            for (int j = 0; j < 4; j++)
                stsm4(st_addr[j] + half * 16384,
                      pack_bf16(fmaf(v[8 * j], inv0, u[8 * j]), fmaf(v[8 * j + 1], inv0, u[8 * j + 1])),
                      pack_bf16(fmaf(v[8 * j + 2], inv1, u[8 * j + 2]), fmaf(v[8 * j + 3], inv1, u[8 * j + 3])),
                      pack_bf16(fmaf(v[8 * j + 4], inv0, u[8 * j + 4]), fmaf(v[8 * j + 5], inv0, u[8 * j + 5])),
                      pack_bf16(fmaf(v[8 * j + 6], inv1, u[8 * j + 6]), fmaf(v[8 * j + 7], inv1, u[8 * j + 7])));
        };
        wg_wait<4>();
        pin(lo);
#pragma unroll
        for (int i = 0; i < 32; i++) lo[i] *= (i & 2) ? fa1 : fa0;
        pin(lo);
        sched_fence(inv0);
        wg_wait<0>();
        pin(x);
        stage_half(lo, x, 0);
        asm volatile("fence.proxy.async.shared::cta;" ::: "memory");
        __syncwarp();
        if (lane == 0) mbar_arrive(bar_staged + 8 * wg);
        tail_units<0, 4>(hi, p, dv_hi, bar_tail + 64);
        tail_units<0, 4, true>(y, qf, dv_hi + (16384 >> 4), bar_tail + 96);
        wg_wait<4>();
        pin(hi);
#pragma unroll
        for (int i = 0; i < 32; i++) hi[i] *= (i & 2) ? fa1 : fa0;
        pin(hi);
        sched_fence(inv0);
        wg_wait<0>();
        pin(y);
#pragma unroll
        for (int e = 0; e < 2; e++) {
            const float inv = e ? inv1 : inv0;
#pragma unroll
            for (int j = 0; j < 2; j++) {
                uint32_t wd[4];
#pragma unroll
                for (int k = 0; k < 4; k++) {
                    const int i = 16 * j + 4 * k + 2 * e;
                    wd[k] = pack_bf16(fmaf(y[i], inv, hi[i]), fmaf(y[i + 1], inv, hi[i + 1]));
                }
                stsm4(stage + 16384 + (8 * e + (lane & 7)) * 128 + (((4 * j + mi) ^ (lane & 7)) << 4), wd[0], wd[1], wd[2], wd[3]);
            }
            __syncwarp();
#pragma unroll
            for (int i = 2 * e; i < 2 * e + 2; i++) {
                uint4 v;
                asm volatile("ld.shared.v4.u32 {%0, %1, %2, %3}, [%4];"
                             : "=r"(v.x), "=r"(v.y), "=r"(v.z), "=r"(v.w) : "r"(ld_addr[i & 1] + (i >> 1) * 1024) : "memory");
                asm volatile("st.global.v4.u32 [%0], {%1, %2, %3, %4};"
                             ::"l"(dst + i * 64), "r"(v.x), "r"(v.y), "r"(v.z), "r"(v.w) : "memory");
            }
        }
    }
}

typedef CUresult (*EncodeFn)(CUtensorMap*, CUtensorMapDataType, cuuint32_t, void*, const cuuint64_t*, const cuuint64_t*,
                             const cuuint32_t*, const cuuint32_t*, CUtensorMapInterleave, CUtensorMapSwizzle,
                             CUtensorMapL2promotion, CUtensorMapFloatOOBfill);

void encode_rows(EncodeFn enc, CUtensorMap* m, void* base, int box_rows) {
    cuuint64_t dims[2] = {(cuuint64_t)kD, (cuuint64_t)kGrid * kRows};
    cuuint64_t strides[1] = {(cuuint64_t)kD * 2};
    cuuint32_t box[2] = {64, (cuuint32_t)box_rows};
    cuuint32_t es[2] = {1, 1};
    enc(m, CU_TENSOR_MAP_DATA_TYPE_BFLOAT16, 2, base, dims, strides, box, es, CU_TENSOR_MAP_INTERLEAVE_NONE,
        CU_TENSOR_MAP_SWIZZLE_128B, CU_TENSOR_MAP_L2_PROMOTION_L2_128B, CU_TENSOR_MAP_FLOAT_OOB_FILL_NONE);
}

void encode_cache(EncodeFn enc, CUtensorMap* m, void* base, int num_phys, int rows, int halves, int groups) {
    cuuint64_t dims[5] = {64, 8, 2, (cuuint64_t)num_phys * 2, (cuuint64_t)kHkv};
    cuuint64_t strides[4] = {(cuuint64_t)kHkv * kD * 2, 128, (cuuint64_t)8 * kHkv * kD * 2, (cuuint64_t)kD * 2};
    cuuint32_t box[5] = {64, (cuuint32_t)rows, (cuuint32_t)halves, (cuuint32_t)groups, 1};
    cuuint32_t es[5] = {1, 1, 1, 1, 1};
    enc(m, CU_TENSOR_MAP_DATA_TYPE_BFLOAT16, 5, base, dims, strides, box, es, CU_TENSOR_MAP_INTERLEAVE_NONE,
        CU_TENSOR_MAP_SWIZZLE_128B, CU_TENSOR_MAP_L2_PROMOTION_L2_128B, CU_TENSOR_MAP_FLOAT_OOB_FILL_NONE);
}

}

extern "C" void kernel_launch(void* const* d_in, const int* in_sizes, int n_in, void* d_out, int out_size) {
    (void)n_in;
    (void)out_size;
    void* fn = nullptr;
    cudaDriverEntryPointQueryResult qr;
    cudaGetDriverEntryPoint("cuTensorMapEncodeTiled", &fn, cudaEnableDefault, &qr);
    EncodeFn enc = (EncodeFn)fn;
    const int num_phys = in_sizes[1] / (kPage * kHkv * kD);
    CUtensorMap mq, mk, mv, mvh, mo, mk4, mv4;
    encode_rows(enc, &mq, d_in[0], kRows);
    encode_rows(enc, &mo, d_out, 64);
    encode_cache(enc, &mk, d_in[1], num_phys, 8, 2, 2);
    encode_cache(enc, &mv, d_in[2], num_phys, 8, 2, 2);
    encode_cache(enc, &mvh, d_in[2], num_phys, 8, 1, 2);
    encode_cache(enc, &mk4, d_in[1], num_phys, 4, 1, 1);
    encode_cache(enc, &mv4, d_in[2], num_phys, 4, 1, 1);
    cudaFuncSetAttribute(paged_attn_kernel, cudaFuncAttributeMaxDynamicSharedMemorySize, kSmemBytes);
    paged_attn_kernel<<<kGrid, kThreads, kSmemBytes>>>((const __nv_bfloat16*)d_in[0], (const int*)d_in[3], (const int*)d_in[4],
                                                       (__nv_bfloat16*)d_out, num_phys, mq, mk, mv, mvh, mo, mk4, mv4);
}
```

```cpp
#include <cuda_runtime.h>
#include <cuda_bf16.h>
#include <cuda.h>
#include <stdint.h>

namespace {

constexpr int kB = 16, kHkv = 8, kD = 128, kPage = 16, kMaxPages = 256;
constexpr int kRows = 128;
constexpr int kTilePages = 8;
constexpr int kSlotBytes = 32768, kPageBytes = 4096;
constexpr int kNumSlots = 7;
constexpr int kTailUnits = 16;
constexpr int kGrid = kB * kHkv;
constexpr int kThreads = 384;
constexpr int kAhead = 18;
constexpr int kTaper = 4, kTaperFrom = 64, kTaperTo = 32;
constexpr int kAheadStart = 6, kFade = 128;
constexpr int kEndPages = 64;
constexpr int kLead = 5;
constexpr int kTau = 4096;
constexpr int kHeadPages = 8;
constexpr int kShared = 3;
constexpr int kSendDelay = 380;
constexpr int kHeldUnits = 3;
constexpr int kBitmapWords = 132;
constexpr uint32_t kUnit = 1u << 25;
static_assert((unsigned long long)kUnit * kGrid == (1ull << 32), "counter must wrap to zero after every launch");

constexpr int kOffRing = 0;
constexpr int kOffMisc = kOffRing + kNumSlots * kSlotBytes;
constexpr int kOffPages = kOffMisc;
constexpr int kOffBitmap = kOffPages + kMaxPages * 4;
constexpr int kOffCounts = kOffBitmap + kBitmapWords * 4;
constexpr int kOffBars = kOffCounts + 256;
constexpr int kOffFlags = kOffBars + (2 * kNumSlots + kTailUnits + 4) * 8;
constexpr int kFlagWords = 6;
constexpr int kSmemBytes = kOffFlags + kFlagWords * 4;
static_assert(kSmemBytes <= 232448 && kOffFlags % 16 == 0, "shared memory budget");

__device__ uint32_t g_progress;

__device__ __forceinline__ uint32_t smem_u32(const void* p) { return (uint32_t)__cvta_generic_to_shared(p); }
__device__ __forceinline__ void mbar_init(uint32_t bar, uint32_t cnt) {
    asm volatile("mbarrier.init.shared::cta.b64 [%0], %1;" ::"r"(bar), "r"(cnt) : "memory");
}
__device__ __forceinline__ void mbar_expect_tx(uint32_t bar, uint32_t bytes) {
    asm volatile("mbarrier.arrive.expect_tx.shared::cta.b64 _, [%0], %1;" ::"r"(bar), "r"(bytes) : "memory");
}
__device__ __forceinline__ void mbar_arrive(uint32_t bar) {
    asm volatile("mbarrier.arrive.shared::cta.b64 _, [%0];" ::"r"(bar) : "memory");
}
__device__ __forceinline__ void mbar_wait(uint32_t bar, uint32_t parity) {
    asm volatile(
        "{ .reg .pred p; .reg .u32 c;\n"
        "mov.u32 c, 0;\n"
        "WAIT_%=: mbarrier.try_wait.parity.shared::cta.b64 p, [%0], %1;\n"
        "@p bra.uni DONE_%=;\n"
        "add.u32 c, c, 1;\n"
        "setp.gt.u32 p, c, 0x1000000;\n"
        "@p trap;\n"
        "bra.uni WAIT_%=;\n"
        "DONE_%=: }"
        ::"r"(bar), "r"(parity) : "memory");
}
__device__ __forceinline__ uint32_t mbar_test(uint32_t bar, uint32_t parity) {
    uint32_t ok;
    asm volatile("{ .reg .pred p; mbarrier.test_wait.parity.shared::cta.b64 p, [%1], %2; selp.u32 %0, 1, 0, p; }"
                 : "=r"(ok) : "r"(bar), "r"(parity) : "memory");
    return ok;
}
__device__ __forceinline__ uint32_t clock_u32() {
    uint32_t c;
    asm volatile("mov.u32 %0, %%clock;" : "=r"(c));
    return c;
}
__device__ __forceinline__ uint32_t clock_after(uint32_t dep) {
    uint32_t c;
    asm volatile("{ .reg .pred p; setp.eq.u32 p, %1, 0xffffffff; mov.u32 %0, 0; @!p mov.u32 %0, %%clock; }" : "=r"(c) : "r"(dep));
    return c;
}
__device__ __forceinline__ void trap_if(bool c) {
    asm volatile("{ .reg .pred p; setp.ne.b32 p, %0, 0; @p trap; }" ::"r"((int)c));
}
__device__ __forceinline__ void sched_fence(float x) {
    asm volatile(
        "{ .reg .pred p; .reg .u32 t;\n"
        "setp.lt.f32 p, %0, 0f00000000;\n"
        "@!p bra D_%=;\n"
        "F_%=: mov.u32 t, %%clock;\n"
        "setp.eq.u32 p, t, 0;\n"
        "@p bra F_%=;\n"
        "D_%=: }" ::"f"(x) : "memory");
}
__device__ __forceinline__ uint32_t lds_volatile(uint32_t a) {
    uint32_t v;
    asm volatile("ld.volatile.shared.u32 %0, [%1];" : "=r"(v) : "r"(a) : "memory");
    return v;
}
__device__ __forceinline__ void sts_volatile(uint32_t a, uint32_t v) {
    asm volatile("st.volatile.shared.u32 [%0], %1;" ::"r"(a), "r"(v) : "memory");
}
__device__ __forceinline__ void tma_load_page(uint32_t dst, const CUtensorMap* map, uint32_t bar, int half, int row8, int head, uint64_t pol, int row = 0) {
    asm volatile(
        "cp.async.bulk.tensor.5d.shared::cluster.global.mbarrier::complete_tx::bytes.L2::cache_hint "
        "[%0], [%1, {%3, %8, %7, %4, %5}], [%2], %6;"
        ::"r"(dst), "l"(map), "r"(bar), "r"(0), "r"(row8), "r"(head), "l"(pol), "r"(half), "r"(row) : "memory");
}
__device__ __forceinline__ void tma_load_2d(uint32_t dst, const CUtensorMap* map, uint32_t bar, int c0, int c1) {
    asm volatile(
        "cp.async.bulk.tensor.2d.shared::cluster.global.mbarrier::complete_tx::bytes [%0], [%1, {%3, %4}], [%2];"
        ::"r"(dst), "l"(map), "r"(bar), "r"(c0), "r"(c1) : "memory");
}
__device__ __forceinline__ void tma_store_2d(const CUtensorMap* map, uint32_t src, int c0, int c1) {
    asm volatile("cp.async.bulk.tensor.2d.global.shared::cta.bulk_group [%0, {%2, %3}], [%1];"
                 ::"l"(map), "r"(src), "r"(c0), "r"(c1) : "memory");
}
__device__ __forceinline__ float ex2(float x) {
    float y;
    asm("ex2.approx.ftz.f32 %0, %1;" : "=f"(y) : "f"(x));
    return y;
}
__device__ __forceinline__ float rcp(float x) {
    float y;
    asm("rcp.approx.ftz.f32 %0, %1;" : "=f"(y) : "f"(x));
    return y;
}
__device__ __forceinline__ uint32_t pack_bf16(float lo, float hi) {
    uint32_t r;
    asm("cvt.rn.bf16x2.f32 %0, %1, %2;" : "=r"(r) : "f"(hi), "f"(lo));
    return r;
}
__device__ __forceinline__ uint32_t desc_lo(uint32_t addr, uint32_t lbo) { return ((addr & 0x3FFFF) >> 4) | ((lbo >> 4) << 16); }
constexpr uint32_t kDescHi = (2048 >> 4) | (1u << 30), kDescHiDense = (1024 >> 4) | (1u << 30);
__device__ __forceinline__ void wg_fence() { asm volatile("wgmma.fence.sync.aligned;" ::: "memory"); }
__device__ __forceinline__ void wg_commit() { asm volatile("wgmma.commit_group.sync.aligned;" ::: "memory"); }
template <int N> __device__ __forceinline__ void wg_wait() { asm volatile("wgmma.wait_group.sync.aligned %0;" ::"n"(N) : "memory"); }
template <int N> __device__ __forceinline__ void wg_wait_release(uint32_t bar, int lane) {
    asm volatile(
        "{ .reg .pred p; setp.eq.s32 p, %2, 0;\n"
        "wgmma.wait_group.sync.aligned %0;\n"
        "@p mbarrier.arrive.shared::cta.b64 _, [%1]; }" ::"n"(N), "r"(bar), "r"(lane) : "memory");
}
template <int N> __device__ __forceinline__ void pin(float (&r)[N]) {
#pragma unroll
    for (int i = 0; i < N; i++) asm volatile("" : "+f"(r[i])::"memory");
}
template <int N> __device__ __forceinline__ void pin(uint32_t (&r)[N]) {
#pragma unroll
    for (int i = 0; i < N; i++) asm volatile("" : "+r"(r[i])::"memory");
}

#define ACC_REGS                                                                        \
    "{%0, %1, %2, %3, %4, %5, %6, %7, %8, %9, %10, %11, %12, %13, %14, %15, "           \
    "%16, %17, %18, %19, %20, %21, %22, %23, %24, %25, %26, %27, %28, %29, %30, %31, "  \
    "%32, %33, %34, %35, %36, %37, %38, %39, %40, %41, %42, %43, %44, %45, %46, %47, "  \
    "%48, %49, %50, %51, %52, %53, %54, %55, %56, %57, %58, %59, %60, %61, %62, %63}"
#define ACC8(d, i) "+f"(d[i]), "+f"(d[i + 1]), "+f"(d[i + 2]), "+f"(d[i + 3]), "+f"(d[i + 4]), "+f"(d[i + 5]), "+f"(d[i + 6]), "+f"(d[i + 7])
#define ACC_OPS(d) ACC8(d, 0), ACC8(d, 8), ACC8(d, 16), ACC8(d, 24), ACC8(d, 32), ACC8(d, 40), ACC8(d, 48), ACC8(d, 56)

template <int kAcc, int kTrans> __device__ __forceinline__ void mma(float (&d)[64], const uint32_t* a, uint32_t db) {
    asm volatile(
        "{ .reg .b64 db; mov.b64 db, {%68, %69};\n"
        "wgmma.mma_async.sync.aligned.m64n128k16.f32.bf16.bf16 " ACC_REGS ", {%64, %65, %66, %67}, db, %70, 1, 1, %71; }"
        : ACC_OPS(d) : "r"(a[0]), "r"(a[1]), "r"(a[2]), "r"(a[3]), "r"(db), "n"(kDescHi), "n"(kAcc), "n"(kTrans));
}
#define HALF_MMA(acc)                                                                                             \
    "{ .reg .b64 db; mov.b64 db, {%36, %37};\n"                                                                   \
    "wgmma.mma_async.sync.aligned.m64n64k16.f32.bf16.bf16 "                                                       \
    "{%0, %1, %2, %3, %4, %5, %6, %7, %8, %9, %10, %11, %12, %13, %14, %15, "                                     \
    "%16, %17, %18, %19, %20, %21, %22, %23, %24, %25, %26, %27, %28, %29, %30, %31}, {%32, %33, %34, %35}, db, " \
    acc ", 1, 1, 1; }"
#define OUT8(d, i) "=f"(d[i]), "=f"(d[i + 1]), "=f"(d[i + 2]), "=f"(d[i + 3]), "=f"(d[i + 4]), "=f"(d[i + 5]), "=f"(d[i + 6]), "=f"(d[i + 7])
template <bool kAcc> __device__ __forceinline__ void mma_half(float (&d)[32], const uint32_t* a, uint32_t db) {
    if (kAcc)
        asm volatile(HALF_MMA("1") : ACC8(d, 0), ACC8(d, 8), ACC8(d, 16), ACC8(d, 24)
                     : "r"(a[0]), "r"(a[1]), "r"(a[2]), "r"(a[3]), "r"(db), "n"(kDescHiDense));
    else
        asm volatile(HALF_MMA("0") : OUT8(d, 0), OUT8(d, 8), OUT8(d, 16), OUT8(d, 24)
                     : "r"(a[0]), "r"(a[1]), "r"(a[2]), "r"(a[3]), "r"(db), "n"(kDescHiDense));
}
template <int J0, int J1, bool kFresh = false>
__device__ __forceinline__ void tail_units(float (&d)[32], const uint32_t (&p)[32], uint32_t db, uint32_t bars) {
#pragma unroll
    for (int j = J0; j < J1; j++) {
        mbar_wait(bars + 8 * j, 0);
        wg_fence();
        if (kFresh && j == 0) mma_half<false>(d, p + 8 * j, db + j * (kPageBytes >> 4));
        else mma_half<true>(d, p + 8 * j, db + j * (kPageBytes >> 4));
        mma_half<true>(d, p + 8 * j + 4, db + j * (kPageBytes >> 4) + (2048 >> 4));
        wg_commit();
    }
}
__device__ __forceinline__ void stsm4(uint32_t addr, uint32_t r0, uint32_t r1, uint32_t r2, uint32_t r3) {
    asm volatile("stmatrix.sync.aligned.m8n8.x4.shared.b16 [%0], {%1, %2, %3, %4};"
                 ::"r"(addr), "r"(r0), "r"(r1), "r"(r2), "r"(r3) : "memory");
}
__device__ __forceinline__ void scale_rows(float (&o)[64], float f0, float f1) {
#pragma unroll
    for (int j = 0; j < 16; j++) {
        o[4 * j] *= f0;
        o[4 * j + 1] *= f0;
        o[4 * j + 2] *= f1;
        o[4 * j + 3] *= f1;
    }
}
__device__ __forceinline__ void issue_qk(float (&s)[64], const uint32_t (&qf)[32], uint32_t dk) {
    mma<0, 0>(s, qf, dk);
#pragma unroll
    for (int k = 1; k < 8; k++) mma<1, 0>(s, qf + 4 * k, dk + (((k >> 2) * 1024 + (k & 3) * 32) >> 4));
}
__device__ __forceinline__ void issue_pv(float (&o)[64], const uint32_t (&p)[32], uint32_t dv) {
#pragma unroll
    for (int k = 0; k < 8; k++) mma<1, 1>(o, p + 4 * k, dv + k * (kPageBytes >> 4));
}

__device__ __forceinline__ void item_of(int i, int nt, int& tile, int& is_v) {
    if (nt >= 3 && (i >> 1) == nt - 2) i ^= 1;
    is_v = (i != 0) & ~i & 1;
    tile = is_v ? (i >> 1) - 1 : (i + 1) >> 1;
}

struct Pace {
    int knee, total;
    uint32_t step, end_step;
    __device__ __forceinline__ Pace(int np, int all_pages) {
        total = 2 * np;
        end_step = (uint32_t)((float)kUnit * ((float)kB / (float)(2 * all_pages)));
        const bool bend = total > 2 * kEndPages && all_pages * 2 > 2 * kEndPages * kB;
        knee = bend ? total - kEndPages : total;
        step = (kUnit - (uint32_t)(total - knee) * end_step) / (uint32_t)knee;
    }
    __device__ __forceinline__ uint32_t at(int c) const {
        return c < knee ? (uint32_t)c * step : kUnit - (uint32_t)(total - c) * end_step;
    }
};

struct Seq {
    bool flat;
    int cl, np, nt;
    int first_pages;
    int nitems;
    int quads;
    bool trim;
    __device__ __forceinline__ explicit Seq(int len) {
        flat = len <= 0;
        cl = flat ? kMaxPages * kPage : min(len, kMaxPages * kPage);
        np = (cl + kPage - 1) >> 4;
        nt = (np + kTilePages - 1) >> 3;
        first_pages = np - (nt - 1) * kTilePages;
        nitems = max(2 * nt, 3);
        quads = (cl - (np - 1) * kPage + 3) >> 2;
        trim = nt >= 4;
    }
};

struct Ring {
    int slot = 0;
    uint32_t phase = 0;
    __device__ __forceinline__ void next() {
        if (++slot == kNumSlots) { slot = 0; phase ^= 1; }
    }
};

template <bool kFirst>
__device__ __forceinline__ void softmax_tile(float (&s)[64], float (&m)[2], float (&l)[2], float (&a)[2], int ncols, int lane) {
    constexpr float c = 0.08838834764831845f * 1.4426950408889634f;
    if (kFirst) {
        const int lim = ncols - 2 * (lane & 3);
#pragma unroll
        for (int i = 0; i < 64; i++) s[i] = (8 * (i >> 2) + (i & 1) < lim) ? s[i] : -INFINITY;
    }
    float mq[2][4];
#pragma unroll
    for (int g = 0; g < 4; g++) {
#pragma unroll
        for (int e = 0; e < 2; e++) {
            mq[e][g] = fmaxf(s[4 * g + 2 * e], s[4 * g + 2 * e + 1]);
#pragma unroll
            for (int j = g + 4; j < 16; j += 4) mq[e][g] = fmaxf(fmaxf(mq[e][g], s[4 * j + 2 * e]), s[4 * j + 2 * e + 1]);
        }
    }
    float mx0 = fmaxf(fmaxf(mq[0][0], mq[0][1]), fmaxf(mq[0][2], mq[0][3]));
    float mx1 = fmaxf(fmaxf(mq[1][0], mq[1][1]), fmaxf(mq[1][2], mq[1][3]));
    mx0 = fmaxf(mx0, __shfl_xor_sync(0xffffffffu, mx0, 1));
    mx1 = fmaxf(mx1, __shfl_xor_sync(0xffffffffu, mx1, 1));
    mx0 = fmaxf(mx0, __shfl_xor_sync(0xffffffffu, mx0, 2));
    mx1 = fmaxf(mx1, __shfl_xor_sync(0xffffffffu, mx1, 2));
    if (!kFirst) {
        mx0 = fmaxf(mx0, m[0]);
        mx1 = fmaxf(mx1, m[1]);
    }
    const float b0 = __fmul_rn(mx0, -c), b1 = __fmul_rn(mx1, -c);
    if (!kFirst) {
        a[0] = ex2(__fadd_rn(__fmul_rn(m[0], c), b0));
        a[1] = ex2(__fadd_rn(__fmul_rn(m[1], c), b1));
    }
    m[0] = mx0;
    m[1] = mx1;
    float r0 = 0.f, r1 = 0.f;
#pragma unroll
    for (int j = 0; j < 16; j++) {
        s[4 * j] = ex2(fmaf(s[4 * j], c, b0));
        s[4 * j + 1] = ex2(fmaf(s[4 * j + 1], c, b0));
        s[4 * j + 2] = ex2(fmaf(s[4 * j + 2], c, b1));
        s[4 * j + 3] = ex2(fmaf(s[4 * j + 3], c, b1));
        r0 += s[4 * j] + s[4 * j + 1];
        r1 += s[4 * j + 2] + s[4 * j + 3];
    }
    if (kFirst) { l[0] = r0; l[1] = r1; }
    else { l[0] = fmaf(l[0], a[0], r0); l[1] = fmaf(l[1], a[1], r1); }
}

__global__ void __launch_bounds__(kThreads, 1)
paged_attn_kernel(const __nv_bfloat16* __restrict__ q, const int* __restrict__ block_table, const int* __restrict__ context_lens,
                  __nv_bfloat16* __restrict__ out, int num_phys,
                  const __grid_constant__ CUtensorMap map_q, const __grid_constant__ CUtensorMap map_k,
                  const __grid_constant__ CUtensorMap map_v, const __grid_constant__ CUtensorMap map_vh,
                  const __grid_constant__ CUtensorMap map_o, const __grid_constant__ CUtensorMap map_k4,
                  const __grid_constant__ CUtensorMap map_v4) {
    extern __shared__ __align__(1024) unsigned char sptr[];
    const uint32_t sbase = smem_u32(sptr);
    const uint32_t bar_full = sbase + kOffBars, bar_empty = bar_full + 8 * kNumSlots, bar_tail = bar_empty + 8 * kNumSlots;
    const uint32_t bar_q = bar_tail + 8 * kTailUnits, bar_qfree = bar_q + 8, bar_staged = bar_qfree + 8;
    const uint32_t s_q = sbase + kOffRing + (kNumSlots - 1) * kSlotBytes;
    const uint32_t s_prog = sbase + kOffFlags, s_rate = s_prog + 8, s_done = s_prog + 12, s_stop = s_prog + 16, s_zero = s_prog + 20;
    int* s_pages = reinterpret_cast<int*>(sptr + kOffPages);
    uint32_t* s_bitmap = reinterpret_cast<uint32_t*>(sptr + kOffBitmap);

    const int tid = threadIdx.x, lane = tid & 31;
    const int bh = blockIdx.x, b = bh >> 3, h = bh & 7;

    int cl_lane, my_page = 0;
    if (tid < 256) {
        asm volatile("ld.global.nc.s32 %0, [%1];" : "=r"(my_page) : "l"(block_table + (uint32_t)(b * kMaxPages + tid)));
        asm volatile("ld.global.nc.s32 %0, [%1];" : "=r"(cl_lane) : "l"(context_lens + b));
    } else {
        asm volatile(
            "{ .reg .pred p; .reg .u32 t;\n"
            "setp.ne.u32 p, %2, 320;\n"
            "@p bra S_%=;\n"
            "cp.async.bulk.prefetch.L2.global [%0], %1;\n"
            "F_%=: mov.u32 t, %%clock;\n"
            "setp.eq.u32 p, t, 0;\n"
            "@p bra F_%=;\n"
            "S_%=: }" ::"l"(q + (size_t)bh * kRows * kD), "r"(32768), "r"(tid) : "memory");
        asm volatile("ld.global.nc.s32 %0, [%1];" : "=r"(cl_lane) : "l"(context_lens + (lane & (kB - 1))));
    }
    const int warp = __shfl_sync(0xffffffffu, tid >> 5, 0);
    uint64_t pol;
    asm("createpolicy.fractional.L2::evict_first.b64 %0, 1.0;" : "=l"(pol));

    if (warp == 8) {
        if (lane == 0) {
            mbar_init(bar_q, 1);
            asm volatile("fence.mbarrier_init.release.cluster;" ::: "memory");
            mbar_expect_tx(bar_q, 32768);
            tma_load_2d(s_q, &map_q, bar_q, 0, bh * kRows);
            tma_load_2d(s_q + 16384, &map_q, bar_q, 64, bh * kRows);
        }
    } else if (warp == 9) {
        if (lane == 0) {
            for (int i = 0; i < kNumSlots; i++) mbar_init(bar_full + 8 * i, 1);
            asm volatile("fence.mbarrier_init.release.cluster;" ::: "memory");
        }
    } else if (warp == 10) {
        if (lane == 0) {
            asm volatile("prefetch.tensormap [%0];" ::"l"(&map_k) : "memory");
            asm volatile("prefetch.tensormap [%0];" ::"l"(&map_v) : "memory");
            asm volatile("prefetch.tensormap [%0];" ::"l"(&map_k4) : "memory");
            asm volatile("prefetch.tensormap [%0];" ::"l"(&map_v4) : "memory");
        }
    } else if (warp == 11) {
        trap_if(sbase & 1023);
        if (lane < kFlagWords) sts_volatile(s_prog + 4 * lane, 0);
        if (lane == 0) {
            for (int i = 0; i < kNumSlots; i++) mbar_init(bar_empty + 8 * i, 9);
            mbar_init(bar_qfree, 8);
            mbar_init(bar_staged, 4);
            mbar_init(bar_staged + 8, 4);
        }
    } else if (tid < kBitmapWords) {
        s_bitmap[tid] = 0;
    }
    __syncthreads();
    if (warp == 9) {
        if (lane == 0) {
            for (int i = 0; i < kTailUnits; i++) mbar_init(bar_tail + 8 * i, 1);
            for (int i = 0; i < kTailUnits; i++) mbar_expect_tx(bar_tail + 8 * i, kPageBytes);
            asm volatile("fence.mbarrier_init.release.cluster;" ::: "memory");
        }
        __syncwarp();
        asm volatile("bar.arrive 2, 320;" ::: "memory");
        asm volatile("bar.arrive 7, 320;" ::: "memory");
    }

    if (warp >= 8) {
        asm volatile("setmaxnreg.dec.sync.aligned.u32 40;");
        const Seq sq(__shfl_sync(0xffffffffu, cl_lane, b + lds_volatile(s_zero)));
        const bool flat = sq.flat, side_fill = sq.trim, by_quads = sq.trim && sq.quads < 4;
        const int np = sq.np, nt = sq.nt, first_pages = sq.first_pages, nitems = sq.nitems, quads = sq.quads;
        const uint32_t tail_pages = nt >= 3 ? 0xffffu : nt == 2 ? 0xff00u | ((1u << first_pages) - 1) : ((1u << first_pages) - 1) << 8;
        const int head = sq.trim && !flat ? kHeadPages : 0;
        if (warp == 11) {
            const int slot = lane >= first_pages;
            const uint32_t dst0 = sbase + kOffRing + slot * kSlotBytes + (lane - slot * first_pages) * kPageBytes;
            uint32_t first = lane < head && !(by_quads && lane == first_pages - 1), dst_r = dst0, full_r = bar_full + 8 * slot;
            asm volatile("" : "+r"(first), "+r"(dst_r), "+r"(full_r));
            asm volatile("bar.sync 7, 320;" ::: "memory");
            if (first) tma_load_page(dst_r, &map_k, full_r, 0, s_pages[lane] * 2, h, pol);
            const int qd = lane >> 1, hf = lane & 1;
            const int page = s_pages[first_pages - 1];
            const uint32_t dst = sbase + kOffRing + (first_pages - 1) * kPageBytes + (qd >> 1) * 2048 + hf * 1024 + (qd & 1) * 512;
            if (by_quads && qd < quads) {
                tma_load_page(dst, &map_k4, bar_full, hf, page * 2 + (qd >> 1), h, pol, (qd & 1) * 4);
                tma_load_page(dst + 2 * kSlotBytes, &map_v4, bar_full + 16, hf, page * 2 + (qd >> 1), h, pol, (qd & 1) * 4);
            }
        }
        const int c_lane = (cl_lane <= 0) ? kMaxPages * kPage : min(cl_lane, kMaxPages * kPage);
        const int all_pages = __reduce_add_sync(0xffffffffu, (lane < kB) ? (c_lane + kPage - 1) / kPage : 0);
        const Pace pace(np, all_pages);
        if (warp == 8 || warp == 11) {
            const uint32_t ahead = (uint32_t)fminf((float)kAhead * (float)pace.end_step, (float)kUnit);
            const uint32_t taper_step = ahead / (kAhead * (kTaperFrom - kTaperTo)) * kTaper;
            const int v0_item = nt == 3 ? 3 : 2;
            Ring r;
            r.slot = warp == 8 ? 0 : kShared;
            for (int i = r.slot; i < nitems; i += (i < kShared - 1) ? 1 : 2) {
                int issued = 8 * i - (i > 0 ? 8 - first_pages : 0) - (nt >= 3 && i > v0_item ? 8 - first_pages : 0);
                if (i == nitems - 1) issued += (min(np, 16) >> 1) - 8;
                const bool tail = i >= nitems - 2;
                const int half = tail ? i - (nitems - 2) : 0;
                int tile, is_v, n, idx;
                bool pending, real;
                item_of(i, nt, tile, is_v);
                if (tail) {
                    n = (min(np, 16) + half) >> 1;
                    idx = nt >= 2 ? (nt == 2 && lane < 8 ? lane : np - 16 + lane) : lane - 8;
                    pending = lane < 16;
                    real = lane < 16 && (tail_pages >> lane & 1);
                } else {
                    n = tile ? kTilePages : first_pages;
                    idx = (tile ? first_pages + (tile - 1) * kTilePages : 0) + lane;
                    pending = lane < (is_v && !side_fill ? kTilePages : n) && !(by_quads && tile == 0 && lane == n - 1) &&
                              !(i < 2 && idx < head);
                    real = lane < n && (is_v || !flat);
                }
                const uint32_t full = tail ? bar_tail + 8 * (8 * half + (lane >> 1)) : bar_full + 8 * r.slot;
                if (i == kNumSlots - 1) mbar_wait(bar_qfree, 0);
                if (i == nitems - 3) {
                    asm volatile("prefetch.tensormap [%0];" ::"l"(&map_vh) : "memory");
                    asm volatile("prefetch.tensormap [%0];" ::"l"(&map_o) : "memory");
                }
                mbar_wait(bar_empty + 8 * r.slot, r.phase ^ 1);
                if (!tail && lane == 0)
                    mbar_expect_tx(full, is_v && !side_fill ? kSlotBytes : n * kPageBytes - (by_quads && tile == 0 ? (4 - quads) * 1024 : 0));
                __syncwarp();
                const uint32_t dst = sbase + kOffRing + r.slot * kSlotBytes + lane * (tail ? kPageBytes / 2 : kPageBytes);
                const CUtensorMap* map = tail ? &map_vh : is_v ? &map_v : &map_k;
                const int mine = issued + min((tail ? lane >> 1 : lane) + 1, n);
                const uint32_t boost = (uint32_t)max(kFade - mine, 0) * (pace.end_step / kFade * kAheadStart);
                const uint32_t taper = (uint32_t)min(max(kTaperFrom - (pace.total - mine), 0), kTaperFrom - kTaperTo) * taper_step;
                uint32_t need = pace.at(mine), room = ahead + boost - taper, dst_r = dst, full_r = full;
                asm volatile("" : "+r"(need), "+r"(room), "+r"(dst_r), "+r"(full_r), "+r"(idx));
                if (i == 0) asm volatile("bar.sync 2, 320;" ::: "memory");
                const int page = real ? s_pages[idx] : num_phys;
                uint32_t it = 0;
                do {
                    uint32_t prog, t_prog, rate, done;
                    asm volatile("ld.volatile.shared.v4.u32 {%0, %1, %2, %3}, [%4];"
                                 : "=r"(prog), "=r"(t_prog), "=r"(rate), "=r"(done) : "r"(s_prog) : "memory");
                    prog += rate * (uint32_t)min(max((int)(clock_u32() - t_prog), 0), 2048);
                    if (pending && (need <= prog + room || mine - (int)done <= kTilePages)) {
                        tma_load_page(dst_r, map, full_r, half, page * 2, h, pol);
                        pending = false;
                    }
                    trap_if(++it > (1u << 26));
                } while (__any_sync(0xffffffffu, pending));
                if (i >= kShared - 1) r.next();
                r.next();
            }
            const bool issued_last = (nitems - 1 < kShared || ((nitems - 1 - kShared) & 1)) == (warp == 8);
            if (lane == 0 && issued_last) {
                sts_volatile(s_stop, 1);
                const uint32_t stage = sbase + kOffRing + (nitems % kNumSlots) * kSlotBytes;
                const uint32_t t0 = clock_u32();
                while (clock_u32() - t0 < kSendDelay) {}
                uint32_t todo = 3, it = 0;
                while (todo) {
                    for (int g = 0; g < 2; g++) {
                        if ((todo >> g & 1) && mbar_test(bar_staged + 8 * g, 0)) {
                            tma_store_2d(&map_o, stage + g * 8192, 0, bh * kRows + g * 64);
                            todo &= ~(1u << g);
                        }
                    }
                    trap_if(++it > (1u << 26));
                }
                asm volatile("cp.async.bulk.commit_group;" ::: "memory");
                asm volatile("cp.async.bulk.wait_group.read 0;" ::: "memory");
            }
        } else if (warp == 9) {
            int done = 0;
            auto report = [&](int n) {
                const uint32_t inc = pace.at(done + n) - pace.at(done);
                done += n;
                if (lane == 0) {
                    sts_volatile(s_done, done);
                    asm volatile("red.relaxed.gpu.global.add.u32 [%0], %1;" ::"l"(&g_progress), "r"(inc) : "memory");
                }
            };
            Ring r;
            for (int i = 0; i < nitems - 2; i++) {
                int tile, is_v;
                item_of(i, nt, tile, is_v);
                mbar_wait(bar_full + 8 * r.slot, r.phase);
                if (lane == 0) mbar_arrive(bar_empty + 8 * r.slot);
                report(tile ? kTilePages : first_pages);
                r.next();
            }
            for (int i = 0; i < kTailUnits / 2; i++) mbar_wait(bar_tail + 8 * i, 0);
            report(min(np, 16) >> 1);
            mbar_wait(bar_tail + 8 * (kTailUnits / 2), 0);
            report(pace.total - done);
        } else if (warp == 10) {
            if (lane == 0) {
                uint32_t it = 0, prev = 0, t_prev = clock_u32(), t_ref = t_prev;
                float f_ref = 0.f, g = 0.f;
                const float lead = (float)kLead * (float)pace.end_step;
                while (!lds_volatile(s_stop)) {
                    uint32_t f;
                    asm volatile("ld.relaxed.gpu.global.u32 %0, [%1];" : "=r"(f) : "l"(&g_progress) : "memory");
                    f >>= 7;
                    uint32_t est = f + (f - min(prev, f));
                    prev = f;
                    const uint32_t t = clock_after(f);
                    const float ff = (float)f, dt = (float)(t - t_prev);
                    t_prev = t;
                    if (f < kUnit / 32) {
                        f_ref = ff;
                        t_ref = t;
                    }
                    if (f < kUnit / 10) {
                        g = (float)est;
                    } else {
                        const float rate = __fdividef(ff - f_ref, (float)(t - t_ref));
                        const float adv = rate * dt;
                        const float target = ff + 0.5f * adv;
                        sts_volatile(s_rate, (uint32_t)fminf(rate, 65536.f));
                        g += adv;
                        g += (target - g) * fminf(dt * (1.f / kTau), 1.f);
                        g = fminf(g, target + lead);
                        est = (uint32_t)g;
                    }
                    asm volatile("st.volatile.shared.v2.u32 [%0], {%1, %2};" ::"r"(s_prog), "r"(est), "r"(t) : "memory");
                    trap_if(++it > (1u << 22));
                }
            }
        }
    } else {
        const int len = cl_lane + (int)lds_volatile(s_zero);
        const uint32_t w = min((uint32_t)my_page >> 5, (uint32_t)kBitmapWords - 1), bit = 1u << (my_page & 31);
        const uint32_t in_sort = tid < kMaxPages - 1 && (len <= 0 || (tid + 1) * kPage < len);
        uint32_t seen, dup;
        asm volatile("{ .reg .pred p; setp.ne.u32 p, %3, 0; mov.u32 %0, 0; @p atom.shared.or.b32 %0, [%1], %2; }"
                     : "=&r"(seen) : "r"(sbase + kOffBitmap + 4 * w), "r"(bit), "r"(in_sort) : "memory");
        asm volatile("{ .reg .pred p, q; setp.ne.u32 p, %1, 0; bar.red.or.pred q, 1, 256, p; selp.u32 %0, 1, 0, q; }"
                     : "=r"(dup) : "r"((seen & bit) | (uint32_t)(num_phys > kBitmapWords * 32)) : "memory");
        const uint32_t grp = w >> 2, sub = w & 3;
        const uint4 va = reinterpret_cast<const uint4*>(s_bitmap)[lane];
        const uint4 vb = reinterpret_cast<const uint4*>(s_bitmap)[grp];
        int incl = __popc(va.x) + __popc(va.y) + __popc(va.z) + __popc(va.w);
        const uint32_t s_cnt = sbase + kOffCounts + warp * 32;
        asm volatile("st.shared.u8 [%0], %1;" ::"r"(s_cnt + lane), "r"(incl) : "memory");
        __syncwarp();
        uint32_t cw[8];
        asm volatile("ld.shared.v4.u32 {%0, %1, %2, %3}, [%4];" : "=r"(cw[0]), "=r"(cw[1]), "=r"(cw[2]), "=r"(cw[3]) : "r"(s_cnt) : "memory");
        asm volatile("ld.shared.v4.u32 {%0, %1, %2, %3}, [%4];" : "=r"(cw[4]), "=r"(cw[5]), "=r"(cw[6]), "=r"(cw[7]) : "r"(s_cnt + 16) : "memory");
        uint32_t acc0 = 0, acc1 = 0;
#pragma unroll
        for (int k = 0; k < 4; k++) {
            acc0 = __dp4a(cw[k], __funnelshift_rc(0x01010101u, 0u, max(8 * (4 * k + 4 - (int)grp), 0)), acc0);
            acc1 = __dp4a(cw[k + 4], __funnelshift_rc(0x01010101u, 0u, max(8 * (4 * k + 20 - (int)grp), 0)), acc1);
        }
        const int below = acc0 + acc1;
        const int rank = below + __popc(vb.x & (sub > 0 ? ~0u : bit - 1)) +
                         __popc(vb.y & (sub > 1 ? ~0u : sub == 1 ? bit - 1 : 0u)) +
                         __popc(vb.z & (sub > 2 ? ~0u : sub == 2 ? bit - 1 : 0u)) + __popc(vb.w & (sub == 3 ? bit - 1 : 0u));
        const Seq sq(__shfl_sync(0xffffffffu, len, 0));
        const bool flat = sq.flat, side_fill = sq.trim;
        const int cl = sq.cl, np = sq.np, nt = sq.nt, first_pages = sq.first_pages, nitems = sq.nitems, quads = sq.quads;
        int pos = dup ? tid : rank;
        if (tid == np - 1) pos = first_pages - 1;
        else if (pos >= first_pages - 1) pos++;
        if (tid < np) s_pages[pos] = my_page;
        asm volatile("bar.arrive 7, 320;" ::: "memory");
        asm volatile("bar.arrive 2, 320;" ::: "memory");
        asm volatile("setmaxnreg.inc.sync.aligned.u32 232;");

        const int wg = warp >> 2;
        const int first_cols = cl - (nt - 1) * kTilePages * kPage;
        const uint32_t dk0 = desc_lo(sbase + kOffRing, 16), dv0 = desc_lo(sbase + kOffRing, 1024);

        float o[64], s[64], m[2], l[2], a[2];
        uint32_t p[32], qf[32];
        Ring r;

        if (side_fill) {
            uint4* v0 = reinterpret_cast<uint4*>(sptr + kOffRing + 2 * kSlotBytes);
            const int quad_of_tid = (tid >> 7) * 2 + ((tid >> 5) & 1);
            if (quad_of_tid >= quads) v0[(first_pages - 1) * 256 + tid] = make_uint4(0, 0, 0, 0);
            for (int pg = first_pages; pg < kTilePages; pg++) v0[pg * 256 + tid] = make_uint4(0, 0, 0, 0);
            asm volatile("fence.proxy.async.shared::cta;" ::: "memory");
        }
        mbar_wait(bar_q, 0);
        {
            const uint32_t qrow = s_q + (warp * 16 + (lane & 15)) * 128;
#pragma unroll
            for (int k = 0; k < 8; k++) {
                const uint32_t addr = qrow + (k >> 2) * 16384 + ((((k & 3) * 2 + (lane >> 4)) ^ (lane & 7)) << 4);
                asm volatile("ldmatrix.sync.aligned.m8n8.x4.shared.b16 {%0, %1, %2, %3}, [%4];"
                             : "=r"(qf[4 * k]), "=r"(qf[4 * k + 1]), "=r"(qf[4 * k + 2]), "=r"(qf[4 * k + 3]) : "r"(addr) : "memory");
            }
            if (flat) {
#pragma unroll
                for (int i = 0; i < 32; i++) qf[i] = 0u;
            }
        }
        pin(qf);
        __syncwarp();
        if (lane == 0) mbar_arrive(bar_qfree);
        mbar_wait(bar_full + 8 * r.slot, r.phase);
        wg_fence();
        issue_qk(s, qf, dk0 + r.slot * (kSlotBytes >> 4));
        wg_commit();
        wg_wait<0>();
        pin(s);
        if (lane == 0) mbar_arrive(bar_empty + 8 * r.slot);
        r.next();
        softmax_tile<true>(s, m, l, a, first_cols, lane);
#pragma unroll
        for (int i = 0; i < 32; i++) p[i] = pack_bf16(s[2 * i], s[2 * i + 1]);
#pragma unroll
        for (int i = 0; i < 64; i++) o[i] = 0.f;
        const bool deep = nt >= 3;
        const int spare = nitems % kNumSlots;
        const uint32_t spare_free = ((nitems / kNumSlots) & 1) ^ 1;
        const uint32_t stage = sbase + kOffRing + spare * kSlotBytes + warp * 2048;
        float a_parked[2] = {1.f, 1.f};
        auto wg_count = [&](bool flag) {
            uint32_t n;
            if (wg == 0)
                asm volatile("{ .reg .pred p; setp.ne.u32 p, %1, 0; bar.red.popc.u32 %0, 3, 128, p; }" : "=r"(n) : "r"((uint32_t)flag) : "memory");
            else
                asm volatile("{ .reg .pred p; setp.ne.u32 p, %1, 0; bar.red.popc.u32 %0, 4, 128, p; }" : "=r"(n) : "r"((uint32_t)flag) : "memory");
            return (int)__shfl_sync(0xffffffffu, n, 0);
        };
        if (wg == 1 && nt > 1) asm volatile("bar.arrive 5, 256;" ::: "memory");

        auto start_scores = [&]() {
            const int ks = r.slot;
            mbar_wait(bar_full + 8 * ks, r.phase);
            r.next();
            if (wg == 0) asm volatile("bar.sync 5, 256;" ::: "memory");
            else asm volatile("bar.sync 6, 256;" ::: "memory");
            pin(o);
            pin(p);
            wg_fence();
            issue_qk(s, qf, dk0 + ks * (kSlotBytes >> 4));
            wg_commit();
            return ks;
        };
        auto pass_turn = [&]() {
            if (wg == 0) asm volatile("bar.arrive 6, 256;" ::: "memory");
            else asm volatile("bar.arrive 5, 256;" ::: "memory");
        };

        for (int t = 1; t < nt - 2; t++) {
            const int ks = start_scores();
            const int vs = r.slot;
            mbar_wait(bar_full + 8 * vs, r.phase);
            r.next();
            wg_fence();
            issue_pv(o, p, dv0 + vs * (kSlotBytes >> 4));
            wg_commit();
            pass_turn();
            wg_wait_release<1>(bar_empty + 8 * ks, lane);
            pin(s);
            softmax_tile<false>(s, m, l, a, 0, lane);
            pin(s);
            sched_fence(l[0] + l[1]);
            wg_wait_release<0>(bar_empty + 8 * vs, lane);
            pin(o);
            pin(p);
            if (__any_sync(0xffffffffu, a[0] != 1.f || a[1] != 1.f)) scale_rows(o, a[0], a[1]);
#pragma unroll
            for (int i = 0; i < 32; i++) p[i] = pack_bf16(s[2 * i], s[2 * i + 1]);
        }
        if (deep) {
            start_scores();
            pass_turn();
            mbar_wait(bar_empty + 8 * spare, spare_free);
            wg_wait<0>();
            pin(s);
            softmax_tile<false>(s, m, l, a_parked, 0, lane);
#pragma unroll
            for (int i = 0; i < 8; i++)
                asm volatile("st.shared.v4.u32 [%0], {%1, %2, %3, %4};"
                             ::"r"(stage + (i >> 2) * 16384 + (i & 3) * 512 + lane * 16),
                               "r"(pack_bf16(s[8 * i], s[8 * i + 1])), "r"(pack_bf16(s[8 * i + 2], s[8 * i + 3])),
                               "r"(pack_bf16(s[8 * i + 4], s[8 * i + 5])), "r"(pack_bf16(s[8 * i + 6], s[8 * i + 7])) : "memory");
        }
        a[0] = a[1] = 1.f;
        if (nt > 1) {
            start_scores();
            const uint32_t v_full = bar_full + 8 * r.slot, v_phase = r.phase, dv = dv0 + r.slot * (kSlotBytes >> 4);
            if (deep) r.next();
            const bool early = deep && wg_count(mbar_test(v_full, v_phase)) == 128;
            if (early) {
                wg_fence();
                issue_pv(o, p, dv);
                wg_commit();
                if (wg == 0) asm volatile("bar.arrive 6, 256;" ::: "memory");
                wg_wait<1>();
            } else {
                if (wg == 0) asm volatile("bar.arrive 6, 256;" ::: "memory");
                wg_wait<0>();
            }
            pin(s);
            pin(qf);
            softmax_tile<false>(s, m, l, a, 0, lane);
#pragma unroll
            for (int i = 0; i < 32; i++) qf[i] = pack_bf16(s[2 * i], s[2 * i + 1]);
            pin(qf);
            if (deep && !early) {
                mbar_wait(v_full, v_phase);
                wg_fence();
                issue_pv(o, p, dv);
                wg_commit();
            }
        } else {
#pragma unroll
            for (int i = 0; i < 32; i++) qf[i] = p[i];
        }

        l[0] += __shfl_xor_sync(0xffffffffu, l[0], 1);
        l[1] += __shfl_xor_sync(0xffffffffu, l[1], 1);
        l[0] += __shfl_xor_sync(0xffffffffu, l[0], 2);
        l[1] += __shfl_xor_sync(0xffffffffu, l[1], 2);
        const float inv0 = rcp(l[0]), inv1 = rcp(l[1]);
        const float fa0 = a[0] * inv0, fa1 = a[1] * inv1;
        const int mi = lane >> 3;
        uint32_t st_addr[4], ld_addr[2], fin_addr[2];
#pragma unroll
        for (int j = 0; j < 4; j++) st_addr[j] = stage + (lane & 15) * 128 + (((2 * j + (lane >> 4)) ^ (lane & 7)) << 4);
#pragma unroll
        for (int j = 0; j < 2; j++) ld_addr[j] = stage + 16384 + (4 * j + mi) * 128 + (((lane & 7) ^ (4 * j + mi)) << 4);
#pragma unroll
        for (int j = 0; j < 2; j++) fin_addr[j] = stage + 16384 + (lane & 7) * 128 + (((4 * j + mi) ^ (lane & 7)) << 4);
        uint4* dst = reinterpret_cast<uint4*>(out) + (size_t)(bh * kRows + warp * 16 + mi) * 16 + 8 + (lane & 7);
        pin(st_addr);
        pin(ld_addr);
        pin(fin_addr);
        asm volatile("" : "+l"(dst));
        const uint32_t dv_lo = dv0 + r.slot * (kSlotBytes >> 4);
        r.next();
        const uint32_t dv_hi = dv0 + r.slot * (kSlotBytes >> 4);
        sched_fence(inv0 + inv1);
        wg_wait<0>();
        pin(o);
        pin(p);
        if (deep) {
#pragma unroll
            for (int i = 0; i < 8; i++)
                asm volatile("ld.shared.v4.u32 {%0, %1, %2, %3}, [%4];"
                             : "=r"(p[4 * i]), "=r"(p[4 * i + 1]), "=r"(p[4 * i + 2]), "=r"(p[4 * i + 3])
                             : "r"(stage + (i >> 2) * 16384 + (i & 3) * 512 + lane * 16) : "memory");
        } else {
            mbar_wait(bar_empty + 8 * spare, spare_free);
        }
        float lo[32], hi[32], x[32], y[32];
#pragma unroll
        for (int i = 0; i < 32; i++) lo[i] = o[i] * a_parked[(i >> 1) & 1];
        pin(lo);
        pin(p);
        tail_units<0, 2>(lo, p, dv_lo, bar_tail);
#pragma unroll
        for (int i = 0; i < 32; i++) hi[i] = o[32 + i] * a_parked[(i >> 1) & 1];
        pin(hi);
        tail_units<2, 4>(lo, p, dv_lo, bar_tail);
        tail_units<0, 4, true>(x, qf, dv_lo + (16384 >> 4), bar_tail + 32);
        static_assert(kHeldUnits >= 1 && kHeldUnits <= 3, "the first unit of y is not held back");
        auto stage_half = [&](const float (&u)[32], const float (&v)[32], const int half) {
#pragma unroll
            for (int j = 0; j < 4; j++)
                stsm4(st_addr[j] + half * 16384,
                      pack_bf16(fmaf(v[8 * j], inv0, u[8 * j]), fmaf(v[8 * j + 1], inv0, u[8 * j + 1])),
                      pack_bf16(fmaf(v[8 * j + 2], inv1, u[8 * j + 2]), fmaf(v[8 * j + 3], inv1, u[8 * j + 3])),
                      pack_bf16(fmaf(v[8 * j + 4], inv0, u[8 * j + 4]), fmaf(v[8 * j + 5], inv0, u[8 * j + 5])),
                      pack_bf16(fmaf(v[8 * j + 6], inv1, u[8 * j + 6]), fmaf(v[8 * j + 7], inv1, u[8 * j + 7])));
        };
        wg_wait<4>();
        pin(lo);
#pragma unroll
        for (int i = 0; i < 32; i++) lo[i] *= (i & 2) ? fa1 : fa0;
        pin(lo);
        sched_fence(inv0);
        wg_wait<0>();
        pin(x);
        stage_half(lo, x, 0);
        asm volatile("fence.proxy.async.shared::cta;" ::: "memory");
        __syncwarp();
        if (lane == 0) mbar_arrive(bar_staged + 8 * wg);
        tail_units<0, 4>(hi, p, dv_hi, bar_tail + 64);
        tail_units<0, 4 - kHeldUnits, true>(y, qf, dv_hi + (16384 >> 4), bar_tail + 96);
        asm volatile("{ .reg .pred p; setp.ne.u32 p, %0, 0; @p bar.sync 8, 256; }" ::"r"(wg) : "memory");
        tail_units<4 - kHeldUnits, 4>(y, qf, dv_hi + (16384 >> 4), bar_tail + 96);
        asm volatile("{ .reg .pred p; setp.eq.u32 p, %0, 0; @p bar.arrive 8, 256; }" ::"r"(wg) : "memory");
        wg_wait<4>();
        pin(hi);
#pragma unroll
        for (int i = 0; i < 32; i++) hi[i] *= (i & 2) ? fa1 : fa0;
        pin(hi);
        sched_fence(inv0);
        wg_wait<0>();
        pin(y);
#pragma unroll
        for (int e = 0; e < 2; e++) {
            const float inv = e ? inv1 : inv0;
#pragma unroll
            for (int j = 0; j < 2; j++) {
                uint32_t wd[4];
#pragma unroll
                for (int k = 0; k < 4; k++) {
                    const int i = 16 * j + 4 * k + 2 * e;
                    wd[k] = pack_bf16(fmaf(y[i], inv, hi[i]), fmaf(y[i + 1], inv, hi[i + 1]));
                }
                stsm4(fin_addr[j] + e * 1024, wd[0], wd[1], wd[2], wd[3]);
            }
            __syncwarp();
#pragma unroll
            for (int i = 2 * e; i < 2 * e + 2; i++) {
                uint4 v;
                asm volatile("ld.shared.v4.u32 {%0, %1, %2, %3}, [%4];"
                             : "=r"(v.x), "=r"(v.y), "=r"(v.z), "=r"(v.w) : "r"(ld_addr[i & 1] + (i >> 1) * 1024) : "memory");
                asm volatile("st.global.v4.u32 [%0], {%1, %2, %3, %4};"
                             ::"l"(dst + i * 64), "r"(v.x), "r"(v.y), "r"(v.z), "r"(v.w) : "memory");
            }
        }
    }
}

typedef CUresult (*EncodeFn)(CUtensorMap*, CUtensorMapDataType, cuuint32_t, void*, const cuuint64_t*, const cuuint64_t*,
                             const cuuint32_t*, const cuuint32_t*, CUtensorMapInterleave, CUtensorMapSwizzle,
                             CUtensorMapL2promotion, CUtensorMapFloatOOBfill);

void encode_rows(EncodeFn enc, CUtensorMap* m, void* base, int box_rows) {
    cuuint64_t dims[2] = {(cuuint64_t)kD, (cuuint64_t)kGrid * kRows};
    cuuint64_t strides[1] = {(cuuint64_t)kD * 2};
    cuuint32_t box[2] = {64, (cuuint32_t)box_rows};
    cuuint32_t es[2] = {1, 1};
    enc(m, CU_TENSOR_MAP_DATA_TYPE_BFLOAT16, 2, base, dims, strides, box, es, CU_TENSOR_MAP_INTERLEAVE_NONE,
        CU_TENSOR_MAP_SWIZZLE_128B, CU_TENSOR_MAP_L2_PROMOTION_L2_128B, CU_TENSOR_MAP_FLOAT_OOB_FILL_NONE);
}

void encode_cache(EncodeFn enc, CUtensorMap* m, void* base, int num_phys, int rows, int halves, int groups) {
    cuuint64_t dims[5] = {64, 8, 2, (cuuint64_t)num_phys * 2, (cuuint64_t)kHkv};
    cuuint64_t strides[4] = {(cuuint64_t)kHkv * kD * 2, 128, (cuuint64_t)8 * kHkv * kD * 2, (cuuint64_t)kD * 2};
    cuuint32_t box[5] = {64, (cuuint32_t)rows, (cuuint32_t)halves, (cuuint32_t)groups, 1};
    cuuint32_t es[5] = {1, 1, 1, 1, 1};
    enc(m, CU_TENSOR_MAP_DATA_TYPE_BFLOAT16, 5, base, dims, strides, box, es, CU_TENSOR_MAP_INTERLEAVE_NONE,
        CU_TENSOR_MAP_SWIZZLE_128B, CU_TENSOR_MAP_L2_PROMOTION_L2_128B, CU_TENSOR_MAP_FLOAT_OOB_FILL_NONE);
}

}

extern "C" void kernel_launch(void* const* d_in, const int* in_sizes, int n_in, void* d_out, int out_size) {
    (void)n_in;
    (void)out_size;
    void* fn = nullptr;
    cudaDriverEntryPointQueryResult qr;
    cudaGetDriverEntryPoint("cuTensorMapEncodeTiled", &fn, cudaEnableDefault, &qr);
    EncodeFn enc = (EncodeFn)fn;
    const int num_phys = in_sizes[1] / (kPage * kHkv * kD);
    CUtensorMap mq, mk, mv, mvh, mo, mk4, mv4;
    encode_rows(enc, &mq, d_in[0], kRows);
    encode_rows(enc, &mo, d_out, 64);
    encode_cache(enc, &mk, d_in[1], num_phys, 8, 2, 2);
    encode_cache(enc, &mv, d_in[2], num_phys, 8, 2, 2);
    encode_cache(enc, &mvh, d_in[2], num_phys, 8, 1, 2);
    encode_cache(enc, &mk4, d_in[1], num_phys, 4, 1, 1);
    encode_cache(enc, &mv4, d_in[2], num_phys, 4, 1, 1);
    cudaFuncSetAttribute(paged_attn_kernel, cudaFuncAttributeMaxDynamicSharedMemorySize, kSmemBytes);
    paged_attn_kernel<<<kGrid, kThreads, kSmemBytes>>>((const __nv_bfloat16*)d_in[0], (const int*)d_in[3], (const int*)d_in[4],
                                                       (__nv_bfloat16*)d_out, num_phys, mq, mk, mv, mvh, mo, mk4, mv4);
}
```

```cpp
#include <cuda_runtime.h>
#include <cuda_bf16.h>
#include <cuda.h>
#include <stdint.h>

namespace {

constexpr int kB = 16, kHkv = 8, kD = 128, kPage = 16, kMaxPages = 256;
constexpr int kRows = 128;
constexpr int kTilePages = 8;
constexpr int kSlotBytes = 32768, kPageBytes = 4096;
constexpr int kNumSlots = 7;
constexpr int kTailUnits = 16;
constexpr int kGrid = kB * kHkv;
constexpr int kThreads = 384;
constexpr int kAhead = 18;
constexpr int kTaper = 4, kTaperFrom = 64, kTaperTo = 32;
constexpr int kAheadStart = 6, kFade = 128;
constexpr int kEndPages = 64;
constexpr int kLead = 5;
constexpr int kTau = 4096;
constexpr int kHeadPages = 8;
constexpr int kShared = 3;
constexpr int kSendDelay = 380;
constexpr int kHeldUnits = 3;
constexpr int kBitmapWords = 132;
constexpr uint32_t kUnit = 1u << 25;
static_assert((unsigned long long)kUnit * kGrid == (1ull << 32), "counter must wrap to zero after every launch");

constexpr int kOffRing = 0;
constexpr int kOffMisc = kOffRing + kNumSlots * kSlotBytes;
constexpr int kOffPages = kOffMisc;
constexpr int kOffBitmap = kOffPages + kMaxPages * 4;
constexpr int kOffCounts = kOffBitmap + kBitmapWords * 4;
constexpr int kOffBars = kOffCounts + 256;
constexpr int kOffFlags = kOffBars + (2 * kNumSlots + kTailUnits + 4) * 8;
constexpr int kFlagWords = 6;
constexpr int kSmemBytes = kOffFlags + kFlagWords * 4;
static_assert(kSmemBytes <= 232448 && kOffFlags % 16 == 0, "shared memory budget");

__device__ uint32_t g_progress;

__device__ __forceinline__ uint32_t smem_u32(const void* p) { return (uint32_t)__cvta_generic_to_shared(p); }
__device__ __forceinline__ void mbar_init(uint32_t bar, uint32_t cnt) {
    asm volatile("mbarrier.init.shared::cta.b64 [%0], %1;" ::"r"(bar), "r"(cnt) : "memory");
}
__device__ __forceinline__ void mbar_expect_tx(uint32_t bar, uint32_t bytes) {
    asm volatile("mbarrier.arrive.expect_tx.shared::cta.b64 _, [%0], %1;" ::"r"(bar), "r"(bytes) : "memory");
}
__device__ __forceinline__ void mbar_arrive(uint32_t bar) {
    asm volatile("mbarrier.arrive.shared::cta.b64 _, [%0];" ::"r"(bar) : "memory");
}
__device__ __forceinline__ void mbar_wait(uint32_t bar, uint32_t parity) {
    asm volatile(
        "{ .reg .pred p; .reg .u32 c;\n"
        "mov.u32 c, 0;\n"
        "WAIT_%=: mbarrier.try_wait.parity.shared::cta.b64 p, [%0], %1;\n"
        "@p bra.uni DONE_%=;\n"
        "add.u32 c, c, 1;\n"
        "setp.gt.u32 p, c, 0x1000000;\n"
        "@p trap;\n"
        "bra.uni WAIT_%=;\n"
        "DONE_%=: }"
        ::"r"(bar), "r"(parity) : "memory");
}
__device__ __forceinline__ uint32_t mbar_test(uint32_t bar, uint32_t parity) {
    uint32_t ok;
    asm volatile("{ .reg .pred p; mbarrier.test_wait.parity.shared::cta.b64 p, [%1], %2; selp.u32 %0, 1, 0, p; }"
                 : "=r"(ok) : "r"(bar), "r"(parity) : "memory");
    return ok;
}
__device__ __forceinline__ uint32_t clock_u32() {
    uint32_t c;
    asm volatile("mov.u32 %0, %%clock;" : "=r"(c));
    return c;
}
__device__ __forceinline__ uint32_t clock_after(uint32_t dep) {
    uint32_t c;
    asm volatile("{ .reg .pred p; setp.eq.u32 p, %1, 0xffffffff; mov.u32 %0, 0; @!p mov.u32 %0, %%clock; }" : "=r"(c) : "r"(dep));
    return c;
}
__device__ __forceinline__ void trap_if(bool c) {
    asm volatile("{ .reg .pred p; setp.ne.b32 p, %0, 0; @p trap; }" ::"r"((int)c));
}
__device__ __forceinline__ void sched_fence(float x) {
    asm volatile(
        "{ .reg .pred p; .reg .u32 t;\n"
        "setp.lt.f32 p, %0, 0f00000000;\n"
        "@!p bra D_%=;\n"
        "F_%=: mov.u32 t, %%clock;\n"
        "setp.eq.u32 p, t, 0;\n"
        "@p bra F_%=;\n"
        "D_%=: }" ::"f"(x) : "memory");
}
__device__ __forceinline__ uint32_t lds_volatile(uint32_t a) {
    uint32_t v;
    asm volatile("ld.volatile.shared.u32 %0, [%1];" : "=r"(v) : "r"(a) : "memory");
    return v;
}
__device__ __forceinline__ void sts_volatile(uint32_t a, uint32_t v) {
    asm volatile("st.volatile.shared.u32 [%0], %1;" ::"r"(a), "r"(v) : "memory");
}
__device__ __forceinline__ void tma_load_page(uint32_t dst, const CUtensorMap* map, uint32_t bar, int half, int row8, int head, uint64_t pol, int row = 0) {
    asm volatile(
        "cp.async.bulk.tensor.5d.shared::cluster.global.mbarrier::complete_tx::bytes.L2::cache_hint "
        "[%0], [%1, {%3, %8, %7, %4, %5}], [%2], %6;"
        ::"r"(dst), "l"(map), "r"(bar), "r"(0), "r"(row8), "r"(head), "l"(pol), "r"(half), "r"(row) : "memory");
}
__device__ __forceinline__ void tma_load_2d(uint32_t dst, const CUtensorMap* map, uint32_t bar, int c0, int c1) {
    asm volatile(
        "cp.async.bulk.tensor.2d.shared::cluster.global.mbarrier::complete_tx::bytes [%0], [%1, {%3, %4}], [%2];"
        ::"r"(dst), "l"(map), "r"(bar), "r"(c0), "r"(c1) : "memory");
}
__device__ __forceinline__ void tma_store_2d(const CUtensorMap* map, uint32_t src, int c0, int c1) {
    asm volatile("cp.async.bulk.tensor.2d.global.shared::cta.bulk_group [%0, {%2, %3}], [%1];"
                 ::"l"(map), "r"(src), "r"(c0), "r"(c1) : "memory");
}
__device__ __forceinline__ float ex2(float x) {
    float y;
    asm("ex2.approx.ftz.f32 %0, %1;" : "=f"(y) : "f"(x));
    return y;
}
__device__ __forceinline__ float rcp(float x) {
    float y;
    asm("rcp.approx.ftz.f32 %0, %1;" : "=f"(y) : "f"(x));
    return y;
}
__device__ __forceinline__ uint32_t pack_bf16(float lo, float hi) {
    uint32_t r;
    asm("cvt.rn.bf16x2.f32 %0, %1, %2;" : "=r"(r) : "f"(hi), "f"(lo));
    return r;
}
__device__ __forceinline__ uint32_t desc_lo(uint32_t addr, uint32_t lbo) { return ((addr & 0x3FFFF) >> 4) | ((lbo >> 4) << 16); }
constexpr uint32_t kDescHi = (2048 >> 4) | (1u << 30), kDescHiDense = (1024 >> 4) | (1u << 30);
__device__ __forceinline__ void wg_fence() { asm volatile("wgmma.fence.sync.aligned;" ::: "memory"); }
__device__ __forceinline__ void wg_commit() { asm volatile("wgmma.commit_group.sync.aligned;" ::: "memory"); }
template <int N> __device__ __forceinline__ void wg_wait() { asm volatile("wgmma.wait_group.sync.aligned %0;" ::"n"(N) : "memory"); }
template <int N> __device__ __forceinline__ void wg_wait_release(uint32_t bar, int lane) {
    asm volatile(
        "{ .reg .pred p; setp.eq.s32 p, %2, 0;\n"
        "wgmma.wait_group.sync.aligned %0;\n"
        "@p mbarrier.arrive.shared::cta.b64 _, [%1]; }" ::"n"(N), "r"(bar), "r"(lane) : "memory");
}
template <int N> __device__ __forceinline__ void pin(float (&r)[N]) {
#pragma unroll
    for (int i = 0; i < N; i++) asm volatile("" : "+f"(r[i])::"memory");
}
template <int N> __device__ __forceinline__ void pin(uint32_t (&r)[N]) {
#pragma unroll
    for (int i = 0; i < N; i++) asm volatile("" : "+r"(r[i])::"memory");
}

#define ACC_REGS                                                                        \
    "{%0, %1, %2, %3, %4, %5, %6, %7, %8, %9, %10, %11, %12, %13, %14, %15, "           \
    "%16, %17, %18, %19, %20, %21, %22, %23, %24, %25, %26, %27, %28, %29, %30, %31, "  \
    "%32, %33, %34, %35, %36, %37, %38, %39, %40, %41, %42, %43, %44, %45, %46, %47, "  \
    "%48, %49, %50, %51, %52, %53, %54, %55, %56, %57, %58, %59, %60, %61, %62, %63}"
#define ACC8(d, i) "+f"(d[i]), "+f"(d[i + 1]), "+f"(d[i + 2]), "+f"(d[i + 3]), "+f"(d[i + 4]), "+f"(d[i + 5]), "+f"(d[i + 6]), "+f"(d[i + 7])
#define ACC_OPS(d) ACC8(d, 0), ACC8(d, 8), ACC8(d, 16), ACC8(d, 24), ACC8(d, 32), ACC8(d, 40), ACC8(d, 48), ACC8(d, 56)

template <int kAcc, int kTrans> __device__ __forceinline__ void mma(float (&d)[64], const uint32_t* a, uint32_t db) {
    asm volatile(
        "{ .reg .b64 db; mov.b64 db, {%68, %69};\n"
        "wgmma.mma_async.sync.aligned.m64n128k16.f32.bf16.bf16 " ACC_REGS ", {%64, %65, %66, %67}, db, %70, 1, 1, %71; }"
        : ACC_OPS(d) : "r"(a[0]), "r"(a[1]), "r"(a[2]), "r"(a[3]), "r"(db), "n"(kDescHi), "n"(kAcc), "n"(kTrans));
}
#define HALF_MMA(acc)                                                                                             \
    "{ .reg .b64 db; mov.b64 db, {%36, %37};\n"                                                                   \
    "wgmma.mma_async.sync.aligned.m64n64k16.f32.bf16.bf16 "                                                       \
    "{%0, %1, %2, %3, %4, %5, %6, %7, %8, %9, %10, %11, %12, %13, %14, %15, "                                     \
    "%16, %17, %18, %19, %20, %21, %22, %23, %24, %25, %26, %27, %28, %29, %30, %31}, {%32, %33, %34, %35}, db, " \
    acc ", 1, 1, 1; }"
#define OUT8(d, i) "=f"(d[i]), "=f"(d[i + 1]), "=f"(d[i + 2]), "=f"(d[i + 3]), "=f"(d[i + 4]), "=f"(d[i + 5]), "=f"(d[i + 6]), "=f"(d[i + 7])
template <bool kAcc> __device__ __forceinline__ void mma_half(float (&d)[32], const uint32_t* a, uint32_t db) {
    if (kAcc)
        asm volatile(HALF_MMA("1") : ACC8(d, 0), ACC8(d, 8), ACC8(d, 16), ACC8(d, 24)
                     : "r"(a[0]), "r"(a[1]), "r"(a[2]), "r"(a[3]), "r"(db), "n"(kDescHiDense));
    else
        asm volatile(HALF_MMA("0") : OUT8(d, 0), OUT8(d, 8), OUT8(d, 16), OUT8(d, 24)
                     : "r"(a[0]), "r"(a[1]), "r"(a[2]), "r"(a[3]), "r"(db), "n"(kDescHiDense));
}
template <int J0, int J1, bool kFresh = false>
__device__ __forceinline__ void tail_units(float (&d)[32], const uint32_t (&p)[32], uint32_t db, uint32_t bars) {
#pragma unroll
    for (int j = J0; j < J1; j++) {
        mbar_wait(bars + 8 * j, 0);
        wg_fence();
        if (kFresh && j == 0) mma_half<false>(d, p + 8 * j, db + j * (kPageBytes >> 4));
        else mma_half<true>(d, p + 8 * j, db + j * (kPageBytes >> 4));
        mma_half<true>(d, p + 8 * j + 4, db + j * (kPageBytes >> 4) + (2048 >> 4));
        wg_commit();
    }
}
__device__ __forceinline__ void stsm4(uint32_t addr, uint32_t r0, uint32_t r1, uint32_t r2, uint32_t r3) {
    asm volatile("stmatrix.sync.aligned.m8n8.x4.shared.b16 [%0], {%1, %2, %3, %4};"
                 ::"r"(addr), "r"(r0), "r"(r1), "r"(r2), "r"(r3) : "memory");
}
__device__ __forceinline__ void scale_rows(float (&o)[64], float f0, float f1) {
#pragma unroll
    for (int j = 0; j < 16; j++) {
        o[4 * j] *= f0;
        o[4 * j + 1] *= f0;
        o[4 * j + 2] *= f1;
        o[4 * j + 3] *= f1;
    }
}
__device__ __forceinline__ void issue_qk(float (&s)[64], const uint32_t (&qf)[32], uint32_t dk) {
    mma<0, 0>(s, qf, dk);
#pragma unroll
    for (int k = 1; k < 8; k++) mma<1, 0>(s, qf + 4 * k, dk + (((k >> 2) * 1024 + (k & 3) * 32) >> 4));
}
__device__ __forceinline__ void issue_pv(float (&o)[64], const uint32_t (&p)[32], uint32_t dv) {
#pragma unroll
    for (int k = 0; k < 8; k++) mma<1, 1>(o, p + 4 * k, dv + k * (kPageBytes >> 4));
}

__device__ __forceinline__ void item_of(int i, int nt, int& tile, int& is_v) {
    if (nt >= 3 && (i >> 1) == nt - 2) i ^= 1;
    is_v = (i != 0) & ~i & 1;
    tile = is_v ? (i >> 1) - 1 : (i + 1) >> 1;
}

struct Pace {
    int knee, total;
    uint32_t step, end_step;
    __device__ __forceinline__ Pace(int np, int all_pages) {
        total = 2 * np;
        end_step = (uint32_t)((float)kUnit * ((float)kB / (float)(2 * all_pages)));
        const bool bend = total > 2 * kEndPages && all_pages * 2 > 2 * kEndPages * kB;
        knee = bend ? total - kEndPages : total;
        step = (kUnit - (uint32_t)(total - knee) * end_step) / (uint32_t)knee;
    }
    __device__ __forceinline__ uint32_t at(int c) const {
        return c < knee ? (uint32_t)c * step : kUnit - (uint32_t)(total - c) * end_step;
    }
};

struct Seq {
    bool flat;
    int cl, np, nt;
    int first_pages;
    int nitems;
    int valid;
    bool trim;
    __device__ __forceinline__ explicit Seq(int len) {
        flat = len <= 0;
        cl = flat ? kMaxPages * kPage : min(len, kMaxPages * kPage);
        np = (cl + kPage - 1) >> 4;
        nt = (np + kTilePages - 1) >> 3;
        first_pages = np - (nt - 1) * kTilePages;
        nitems = max(2 * nt, 3);
        valid = cl - (np - 1) * kPage;
        trim = nt >= 4;
    }
};

struct Ring {
    int slot = 0;
    uint32_t phase = 0;
    __device__ __forceinline__ void next() {
        if (++slot == kNumSlots) { slot = 0; phase ^= 1; }
    }
};

template <bool kFirst>
__device__ __forceinline__ void softmax_tile(float (&s)[64], float (&m)[2], float (&l)[2], float (&a)[2], int ncols, int lane) {
    constexpr float c = 0.08838834764831845f * 1.4426950408889634f;
    if (kFirst) {
        const int lim = ncols - 2 * (lane & 3);
#pragma unroll
        for (int i = 0; i < 64; i++) s[i] = (8 * (i >> 2) + (i & 1) < lim) ? s[i] : -INFINITY;
    }
    float mq[2][4];
#pragma unroll
    for (int g = 0; g < 4; g++) {
#pragma unroll
        for (int e = 0; e < 2; e++) {
            mq[e][g] = fmaxf(s[4 * g + 2 * e], s[4 * g + 2 * e + 1]);
#pragma unroll
            for (int j = g + 4; j < 16; j += 4) mq[e][g] = fmaxf(fmaxf(mq[e][g], s[4 * j + 2 * e]), s[4 * j + 2 * e + 1]);
        }
    }
    float mx0 = fmaxf(fmaxf(mq[0][0], mq[0][1]), fmaxf(mq[0][2], mq[0][3]));
    float mx1 = fmaxf(fmaxf(mq[1][0], mq[1][1]), fmaxf(mq[1][2], mq[1][3]));
    mx0 = fmaxf(mx0, __shfl_xor_sync(0xffffffffu, mx0, 1));
    mx1 = fmaxf(mx1, __shfl_xor_sync(0xffffffffu, mx1, 1));
    mx0 = fmaxf(mx0, __shfl_xor_sync(0xffffffffu, mx0, 2));
    mx1 = fmaxf(mx1, __shfl_xor_sync(0xffffffffu, mx1, 2));
    if (!kFirst) {
        mx0 = fmaxf(mx0, m[0]);
        mx1 = fmaxf(mx1, m[1]);
    }
    const float b0 = __fmul_rn(mx0, -c), b1 = __fmul_rn(mx1, -c);
    if (!kFirst) {
        a[0] = ex2(__fadd_rn(__fmul_rn(m[0], c), b0));
        a[1] = ex2(__fadd_rn(__fmul_rn(m[1], c), b1));
    }
    m[0] = mx0;
    m[1] = mx1;
    float r0 = 0.f, r1 = 0.f;
#pragma unroll
    for (int j = 0; j < 16; j++) {
        s[4 * j] = ex2(fmaf(s[4 * j], c, b0));
        s[4 * j + 1] = ex2(fmaf(s[4 * j + 1], c, b0));
        s[4 * j + 2] = ex2(fmaf(s[4 * j + 2], c, b1));
        s[4 * j + 3] = ex2(fmaf(s[4 * j + 3], c, b1));
        r0 += s[4 * j] + s[4 * j + 1];
        r1 += s[4 * j + 2] + s[4 * j + 3];
    }
    if (kFirst) { l[0] = r0; l[1] = r1; }
    else { l[0] = fmaf(l[0], a[0], r0); l[1] = fmaf(l[1], a[1], r1); }
}

__global__ void __launch_bounds__(kThreads, 1)
paged_attn_kernel(const __nv_bfloat16* __restrict__ q, const int* __restrict__ block_table, const int* __restrict__ context_lens,
                  __nv_bfloat16* __restrict__ out, int num_phys,
                  const __grid_constant__ CUtensorMap map_q, const __grid_constant__ CUtensorMap map_k,
                  const __grid_constant__ CUtensorMap map_v, const __grid_constant__ CUtensorMap map_vh,
                  const __grid_constant__ CUtensorMap map_o, const __grid_constant__ CUtensorMap map_kp,
                  const __grid_constant__ CUtensorMap map_vp) {
    extern __shared__ __align__(1024) unsigned char sptr[];
    const uint32_t sbase = smem_u32(sptr);
    const uint32_t bar_full = sbase + kOffBars, bar_empty = bar_full + 8 * kNumSlots, bar_tail = bar_empty + 8 * kNumSlots;
    const uint32_t bar_q = bar_tail + 8 * kTailUnits, bar_qfree = bar_q + 8, bar_staged = bar_qfree + 8;
    const uint32_t s_q = sbase + kOffRing + (kNumSlots - 1) * kSlotBytes;
    const uint32_t s_prog = sbase + kOffFlags, s_rate = s_prog + 8, s_done = s_prog + 12, s_stop = s_prog + 16, s_zero = s_prog + 20;
    int* s_pages = reinterpret_cast<int*>(sptr + kOffPages);
    uint32_t* s_bitmap = reinterpret_cast<uint32_t*>(sptr + kOffBitmap);

    const int tid = threadIdx.x, lane = tid & 31;
    const int bh = blockIdx.x, b = bh >> 3, h = bh & 7;

    int cl_lane, my_page = 0;
    if (tid < 256) {
        asm volatile("ld.global.nc.s32 %0, [%1];" : "=r"(my_page) : "l"(block_table + (uint32_t)(b * kMaxPages + tid)));
        asm volatile("ld.global.nc.s32 %0, [%1];" : "=r"(cl_lane) : "l"(context_lens + b));
    } else {
        asm volatile(
            "{ .reg .pred p; .reg .u32 t;\n"
            "setp.ne.u32 p, %2, 320;\n"
            "@p bra S_%=;\n"
            "cp.async.bulk.prefetch.L2.global [%0], %1;\n"
            "F_%=: mov.u32 t, %%clock;\n"
            "setp.eq.u32 p, t, 0;\n"
            "@p bra F_%=;\n"
            "S_%=: }" ::"l"(q + (size_t)bh * kRows * kD), "r"(32768), "r"(tid) : "memory");
        asm volatile("ld.global.nc.s32 %0, [%1];" : "=r"(cl_lane) : "l"(context_lens + (lane & (kB - 1))));
    }
    const int warp = __shfl_sync(0xffffffffu, tid >> 5, 0);
    uint64_t pol;
    asm("createpolicy.fractional.L2::evict_first.b64 %0, 1.0;" : "=l"(pol));

    if (warp == 8) {
        if (lane == 0) {
            mbar_init(bar_q, 1);
            asm volatile("fence.mbarrier_init.release.cluster;" ::: "memory");
            mbar_expect_tx(bar_q, 32768);
            tma_load_2d(s_q, &map_q, bar_q, 0, bh * kRows);
            tma_load_2d(s_q + 16384, &map_q, bar_q, 64, bh * kRows);
        }
    } else if (warp == 9) {
        if (lane == 0) {
            for (int i = 0; i < kNumSlots; i++) mbar_init(bar_full + 8 * i, 1);
            asm volatile("fence.mbarrier_init.release.cluster;" ::: "memory");
        }
    } else if (warp == 10) {
        if (lane == 0) {
            asm volatile("prefetch.tensormap [%0];" ::"l"(&map_k) : "memory");
            asm volatile("prefetch.tensormap [%0];" ::"l"(&map_v) : "memory");
            asm volatile("prefetch.tensormap [%0];" ::"l"(&map_kp) : "memory");
            asm volatile("prefetch.tensormap [%0];" ::"l"(&map_vp) : "memory");
        }
    } else if (warp == 11) {
        trap_if(sbase & 1023);
        if (lane < kFlagWords) sts_volatile(s_prog + 4 * lane, 0);
        if (lane == 0) {
            for (int i = 0; i < kNumSlots; i++) mbar_init(bar_empty + 8 * i, 9);
            mbar_init(bar_qfree, 8);
            mbar_init(bar_staged, 4);
            mbar_init(bar_staged + 8, 4);
        }
    } else if (tid < kBitmapWords) {
        s_bitmap[tid] = 0;
    }
    __syncthreads();
    if (warp == 9) {
        if (lane == 0) {
            for (int i = 0; i < kTailUnits; i++) mbar_init(bar_tail + 8 * i, 1);
            for (int i = 0; i < kTailUnits; i++) mbar_expect_tx(bar_tail + 8 * i, kPageBytes);
            asm volatile("fence.mbarrier_init.release.cluster;" ::: "memory");
        }
        __syncwarp();
        asm volatile("bar.arrive 2, 320;" ::: "memory");
        asm volatile("bar.arrive 7, 320;" ::: "memory");
    }

    if (warp >= 8) {
        asm volatile("setmaxnreg.dec.sync.aligned.u32 40;");
        const Seq sq(__shfl_sync(0xffffffffu, cl_lane, b + lds_volatile(s_zero)));
        const bool flat = sq.flat, side_fill = sq.trim, partial = sq.trim && sq.valid < kPage;
        const int np = sq.np, nt = sq.nt, first_pages = sq.first_pages, nitems = sq.nitems;
        const uint32_t tail_pages = nt >= 3 ? 0xffffu : nt == 2 ? 0xff00u | ((1u << first_pages) - 1) : ((1u << first_pages) - 1) << 8;
        const int head = sq.trim && !flat ? kHeadPages : 0;
        if (warp == 11) {
            const int slot = lane >= first_pages;
            const uint32_t dst0 = sbase + kOffRing + slot * kSlotBytes + (lane - slot * first_pages) * kPageBytes;
            uint32_t first = lane < head && !(partial && lane == first_pages - 1), dst_r = dst0, full_r = bar_full + 8 * slot;
            asm volatile("" : "+r"(first), "+r"(dst_r), "+r"(full_r));
            asm volatile("bar.sync 7, 320;" ::: "memory");
            if (first) tma_load_page(dst_r, &map_k, full_r, 0, s_pages[lane] * 2, h, pol);
            const int start = s_pages[first_pages - 1] * kPage + 8 * lane;
            const int skip = start ? 8 - min(max(sq.valid - 8 * lane, 0), 8) : 0;
            const uint32_t dst = sbase + kOffRing + (first_pages - 1) * kPageBytes + lane * 2048;
            if (partial && lane < 2) {
                tma_load_page(dst, &map_kp, bar_full, 0, start - skip, h, pol, skip);
                tma_load_page(dst + 2 * kSlotBytes, &map_vp, bar_full + 16, 0, start - skip, h, pol, skip);
            }
        }
        const int c_lane = (cl_lane <= 0) ? kMaxPages * kPage : min(cl_lane, kMaxPages * kPage);
        const int all_pages = __reduce_add_sync(0xffffffffu, (lane < kB) ? (c_lane + kPage - 1) / kPage : 0);
        const Pace pace(np, all_pages);
        if (warp == 8 || warp == 11) {
            const uint32_t ahead = (uint32_t)fminf((float)kAhead * (float)pace.end_step, (float)kUnit);
            const uint32_t taper_step = ahead / (kAhead * (kTaperFrom - kTaperTo)) * kTaper;
            const int v0_item = nt == 3 ? 3 : 2;
            Ring r;
            r.slot = warp == 8 ? 0 : kShared;
            for (int i = r.slot; i < nitems; i += (i < kShared - 1) ? 1 : 2) {
                int issued = 8 * i - (i > 0 ? 8 - first_pages : 0) - (nt >= 3 && i > v0_item ? 8 - first_pages : 0);
                if (i == nitems - 1) issued += (min(np, 16) >> 1) - 8;
                const bool tail = i >= nitems - 2;
                const int half = tail ? i - (nitems - 2) : 0;
                int tile, is_v, n, idx;
                bool pending, real;
                item_of(i, nt, tile, is_v);
                if (tail) {
                    n = (min(np, 16) + half) >> 1;
                    idx = nt >= 2 ? (nt == 2 && lane < 8 ? lane : np - 16 + lane) : lane - 8;
                    pending = lane < 16;
                    real = lane < 16 && (tail_pages >> lane & 1);
                } else {
                    n = tile ? kTilePages : first_pages;
                    idx = (tile ? first_pages + (tile - 1) * kTilePages : 0) + lane;
                    pending = lane < (is_v && !side_fill ? kTilePages : n) && !(partial && tile == 0 && lane == n - 1) &&
                              !(i < 2 && idx < head);
                    real = lane < n && (is_v || !flat);
                }
                const uint32_t full = tail ? bar_tail + 8 * (8 * half + (lane >> 1)) : bar_full + 8 * r.slot;
                if (i == kNumSlots - 1) mbar_wait(bar_qfree, 0);
                if (i == nitems - 3) {
                    asm volatile("prefetch.tensormap [%0];" ::"l"(&map_vh) : "memory");
                    asm volatile("prefetch.tensormap [%0];" ::"l"(&map_o) : "memory");
                }
                mbar_wait(bar_empty + 8 * r.slot, r.phase ^ 1);
                if (!tail && lane == 0)
                    mbar_expect_tx(full, is_v && !side_fill ? kSlotBytes : n * kPageBytes);
                __syncwarp();
                const uint32_t dst = sbase + kOffRing + r.slot * kSlotBytes + lane * (tail ? kPageBytes / 2 : kPageBytes);
                const CUtensorMap* map = tail ? &map_vh : is_v ? &map_v : &map_k;
                const int mine = issued + min((tail ? lane >> 1 : lane) + 1, n);
                const uint32_t boost = (uint32_t)max(kFade - mine, 0) * (pace.end_step / kFade * kAheadStart);
                const uint32_t taper = (uint32_t)min(max(kTaperFrom - (pace.total - mine), 0), kTaperFrom - kTaperTo) * taper_step;
                uint32_t need = pace.at(mine), room = ahead + boost - taper, dst_r = dst, full_r = full;
                asm volatile("" : "+r"(need), "+r"(room), "+r"(dst_r), "+r"(full_r), "+r"(idx));
                if (i == 0) asm volatile("bar.sync 2, 320;" ::: "memory");
                const int page = real ? s_pages[idx] : num_phys;
                uint32_t it = 0;
                do {
                    uint32_t prog, t_prog, rate, done;
                    asm volatile("ld.volatile.shared.v4.u32 {%0, %1, %2, %3}, [%4];"
                                 : "=r"(prog), "=r"(t_prog), "=r"(rate), "=r"(done) : "r"(s_prog) : "memory");
                    prog += rate * (uint32_t)min(max((int)(clock_u32() - t_prog), 0), 2048);
                    if (pending && (need <= prog + room || mine - (int)done <= kTilePages)) {
                        tma_load_page(dst_r, map, full_r, half, page * 2, h, pol);
                        pending = false;
                    }
                    trap_if(++it > (1u << 26));
                } while (__any_sync(0xffffffffu, pending));
                if (i >= kShared - 1) r.next();
                r.next();
            }
            const bool issued_last = (nitems - 1 < kShared || ((nitems - 1 - kShared) & 1)) == (warp == 8);
            if (lane == 0 && issued_last) {
                sts_volatile(s_stop, 1);
                const uint32_t stage = sbase + kOffRing + (nitems % kNumSlots) * kSlotBytes;
                const uint32_t t0 = clock_u32();
                while (clock_u32() - t0 < kSendDelay) {}
                uint32_t todo = 3, it = 0;
                while (todo) {
                    for (int g = 0; g < 2; g++) {
                        if ((todo >> g & 1) && mbar_test(bar_staged + 8 * g, 0)) {
                            tma_store_2d(&map_o, stage + g * 8192, 0, bh * kRows + g * 64);
                            todo &= ~(1u << g);
                        }
                    }
                    trap_if(++it > (1u << 26));
                }
                asm volatile("cp.async.bulk.commit_group;" ::: "memory");
                asm volatile("cp.async.bulk.wait_group.read 0;" ::: "memory");
            }
        } else if (warp == 9) {
            int done = 0;
            auto report = [&](int n) {
                const uint32_t inc = pace.at(done + n) - pace.at(done);
                done += n;
                if (lane == 0) {
                    sts_volatile(s_done, done);
                    asm volatile("red.relaxed.gpu.global.add.u32 [%0], %1;" ::"l"(&g_progress), "r"(inc) : "memory");
                }
            };
            Ring r;
            for (int i = 0; i < nitems - 2; i++) {
                int tile, is_v;
                item_of(i, nt, tile, is_v);
                mbar_wait(bar_full + 8 * r.slot, r.phase);
                if (lane == 0) mbar_arrive(bar_empty + 8 * r.slot);
                report(tile ? kTilePages : first_pages);
                r.next();
            }
            for (int i = 0; i < kTailUnits / 2; i++) mbar_wait(bar_tail + 8 * i, 0);
            report(min(np, 16) >> 1);
            mbar_wait(bar_tail + 8 * (kTailUnits / 2), 0);
            report(pace.total - done);
        } else if (warp == 10) {
            if (lane == 0) {
                uint32_t it = 0, prev = 0, t_prev = clock_u32(), t_ref = t_prev;
                float f_ref = 0.f, g = 0.f;
                const float lead = (float)kLead * (float)pace.end_step;
                while (!lds_volatile(s_stop)) {
                    uint32_t f;
                    asm volatile("ld.relaxed.gpu.global.u32 %0, [%1];" : "=r"(f) : "l"(&g_progress) : "memory");
                    f >>= 7;
                    uint32_t est = f + (f - min(prev, f));
                    prev = f;
                    const uint32_t t = clock_after(f);
                    const float ff = (float)f, dt = (float)(t - t_prev);
                    t_prev = t;
                    if (f < kUnit / 32) {
                        f_ref = ff;
                        t_ref = t;
                    }
                    if (f < kUnit / 10) {
                        g = (float)est;
                    } else {
                        const float rate = __fdividef(ff - f_ref, (float)(t - t_ref));
                        const float adv = rate * dt;
                        const float target = ff + 0.5f * adv;
                        sts_volatile(s_rate, (uint32_t)fminf(rate, 65536.f));
                        g += adv;
                        g += (target - g) * fminf(dt * (1.f / kTau), 1.f);
                        g = fminf(g, target + lead);
                        est = (uint32_t)g;
                    }
                    asm volatile("st.volatile.shared.v2.u32 [%0], {%1, %2};" ::"r"(s_prog), "r"(est), "r"(t) : "memory");
                    trap_if(++it > (1u << 22));
                }
            }
        }
    } else {
        const int len = cl_lane + (int)lds_volatile(s_zero);
        const uint32_t w = min((uint32_t)my_page >> 5, (uint32_t)kBitmapWords - 1), bit = 1u << (my_page & 31);
        const uint32_t in_sort = tid < kMaxPages - 1 && (len <= 0 || (tid + 1) * kPage < len);
        uint32_t seen, dup;
        asm volatile("{ .reg .pred p; setp.ne.u32 p, %3, 0; mov.u32 %0, 0; @p atom.shared.or.b32 %0, [%1], %2; }"
                     : "=&r"(seen) : "r"(sbase + kOffBitmap + 4 * w), "r"(bit), "r"(in_sort) : "memory");
        asm volatile("{ .reg .pred p, q; setp.ne.u32 p, %1, 0; bar.red.or.pred q, 1, 256, p; selp.u32 %0, 1, 0, q; }"
                     : "=r"(dup) : "r"((seen & bit) | (uint32_t)(num_phys > kBitmapWords * 32)) : "memory");
        const uint32_t grp = w >> 2, sub = w & 3;
        const uint4 va = reinterpret_cast<const uint4*>(s_bitmap)[lane];
        const uint4 vb = reinterpret_cast<const uint4*>(s_bitmap)[grp];
        int incl = __popc(va.x) + __popc(va.y) + __popc(va.z) + __popc(va.w);
        const uint32_t s_cnt = sbase + kOffCounts + warp * 32;
        asm volatile("st.shared.u8 [%0], %1;" ::"r"(s_cnt + lane), "r"(incl) : "memory");
        __syncwarp();
        uint32_t cw[8];
        asm volatile("ld.shared.v4.u32 {%0, %1, %2, %3}, [%4];" : "=r"(cw[0]), "=r"(cw[1]), "=r"(cw[2]), "=r"(cw[3]) : "r"(s_cnt) : "memory");
        asm volatile("ld.shared.v4.u32 {%0, %1, %2, %3}, [%4];" : "=r"(cw[4]), "=r"(cw[5]), "=r"(cw[6]), "=r"(cw[7]) : "r"(s_cnt + 16) : "memory");
        uint32_t acc0 = 0, acc1 = 0;
#pragma unroll
        for (int k = 0; k < 4; k++) {
            acc0 = __dp4a(cw[k], __funnelshift_rc(0x01010101u, 0u, max(8 * (4 * k + 4 - (int)grp), 0)), acc0);
            acc1 = __dp4a(cw[k + 4], __funnelshift_rc(0x01010101u, 0u, max(8 * (4 * k + 20 - (int)grp), 0)), acc1);
        }
        const int below = acc0 + acc1;
        const int rank = below + __popc(vb.x & (sub > 0 ? ~0u : bit - 1)) +
                         __popc(vb.y & (sub > 1 ? ~0u : sub == 1 ? bit - 1 : 0u)) +
                         __popc(vb.z & (sub > 2 ? ~0u : sub == 2 ? bit - 1 : 0u)) + __popc(vb.w & (sub == 3 ? bit - 1 : 0u));
        const Seq sq(__shfl_sync(0xffffffffu, len, 0));
        const bool flat = sq.flat, side_fill = sq.trim;
        const int cl = sq.cl, np = sq.np, nt = sq.nt, first_pages = sq.first_pages, nitems = sq.nitems;
        int pos = dup ? tid : rank;
        if (tid == np - 1) pos = first_pages - 1;
        else if (pos >= first_pages - 1) pos++;
        if (tid < np) s_pages[pos] = my_page;
        asm volatile("bar.arrive 7, 320;" ::: "memory");
        asm volatile("bar.arrive 2, 320;" ::: "memory");
        asm volatile("setmaxnreg.inc.sync.aligned.u32 232;");

        const int wg = warp >> 2;
        const int first_cols = cl - (nt - 1) * kTilePages * kPage;
        const uint32_t dk0 = desc_lo(sbase + kOffRing, 16), dv0 = desc_lo(sbase + kOffRing, 1024);

        float o[64], s[64], m[2], l[2], a[2];
        uint32_t p[32], qf[32];
        Ring r;

        if (side_fill) {
            uint4* v0 = reinterpret_cast<uint4*>(sptr + kOffRing + 2 * kSlotBytes);
            for (int pg = first_pages; pg < kTilePages; pg++) v0[pg * 256 + tid] = make_uint4(0, 0, 0, 0);
            asm volatile("fence.proxy.async.shared::cta;" ::: "memory");
        }
        mbar_wait(bar_q, 0);
        {
            const uint32_t qrow = s_q + (warp * 16 + (lane & 15)) * 128;
#pragma unroll
            for (int k = 0; k < 8; k++) {
                const uint32_t addr = qrow + (k >> 2) * 16384 + ((((k & 3) * 2 + (lane >> 4)) ^ (lane & 7)) << 4);
                asm volatile("ldmatrix.sync.aligned.m8n8.x4.shared.b16 {%0, %1, %2, %3}, [%4];"
                             : "=r"(qf[4 * k]), "=r"(qf[4 * k + 1]), "=r"(qf[4 * k + 2]), "=r"(qf[4 * k + 3]) : "r"(addr) : "memory");
            }
            if (flat) {
#pragma unroll
                for (int i = 0; i < 32; i++) qf[i] = 0u;
            }
        }
        pin(qf);
        __syncwarp();
        if (lane == 0) mbar_arrive(bar_qfree);
        mbar_wait(bar_full + 8 * r.slot, r.phase);
        wg_fence();
        issue_qk(s, qf, dk0 + r.slot * (kSlotBytes >> 4));
        wg_commit();
        wg_wait<0>();
        pin(s);
        if (lane == 0) mbar_arrive(bar_empty + 8 * r.slot);
        r.next();
        softmax_tile<true>(s, m, l, a, first_cols, lane);
#pragma unroll
        for (int i = 0; i < 32; i++) p[i] = pack_bf16(s[2 * i], s[2 * i + 1]);
#pragma unroll
        for (int i = 0; i < 64; i++) o[i] = 0.f;
        const bool deep = nt >= 3;
        const int spare = nitems % kNumSlots;
        const uint32_t spare_free = ((nitems / kNumSlots) & 1) ^ 1;
        const uint32_t stage = sbase + kOffRing + spare * kSlotBytes + warp * 2048;
        float a_parked[2] = {1.f, 1.f};
        auto wg_count = [&](bool flag) {
            uint32_t n;
            if (wg == 0)
                asm volatile("{ .reg .pred p; setp.ne.u32 p, %1, 0; bar.red.popc.u32 %0, 3, 128, p; }" : "=r"(n) : "r"((uint32_t)flag) : "memory");
            else
                asm volatile("{ .reg .pred p; setp.ne.u32 p, %1, 0; bar.red.popc.u32 %0, 4, 128, p; }" : "=r"(n) : "r"((uint32_t)flag) : "memory");
            return (int)__shfl_sync(0xffffffffu, n, 0);
        };
        if (wg == 1 && nt > 1) asm volatile("bar.arrive 5, 256;" ::: "memory");

        auto start_scores = [&]() {
            const int ks = r.slot;
            mbar_wait(bar_full + 8 * ks, r.phase);
            r.next();
            if (wg == 0) asm volatile("bar.sync 5, 256;" ::: "memory");
            else asm volatile("bar.sync 6, 256;" ::: "memory");
            pin(o);
            pin(p);
            wg_fence();
            issue_qk(s, qf, dk0 + ks * (kSlotBytes >> 4));
            wg_commit();
            return ks;
        };
        auto pass_turn = [&]() {
            if (wg == 0) asm volatile("bar.arrive 6, 256;" ::: "memory");
            else asm volatile("bar.arrive 5, 256;" ::: "memory");
        };

        for (int t = 1; t < nt - 2; t++) {
            const int ks = start_scores();
            const int vs = r.slot;
            mbar_wait(bar_full + 8 * vs, r.phase);
            r.next();
            wg_fence();
            issue_pv(o, p, dv0 + vs * (kSlotBytes >> 4));
            wg_commit();
            pass_turn();
            wg_wait_release<1>(bar_empty + 8 * ks, lane);
            pin(s);
            softmax_tile<false>(s, m, l, a, 0, lane);
            pin(s);
            sched_fence(l[0] + l[1]);
            wg_wait_release<0>(bar_empty + 8 * vs, lane);
            pin(o);
            pin(p);
            if (__any_sync(0xffffffffu, a[0] != 1.f || a[1] != 1.f)) scale_rows(o, a[0], a[1]);
#pragma unroll
            for (int i = 0; i < 32; i++) p[i] = pack_bf16(s[2 * i], s[2 * i + 1]);
        }
        if (deep) {
            start_scores();
            pass_turn();
            mbar_wait(bar_empty + 8 * spare, spare_free);
            wg_wait<0>();
            pin(s);
            softmax_tile<false>(s, m, l, a_parked, 0, lane);
#pragma unroll
            for (int i = 0; i < 8; i++)
                asm volatile("st.shared.v4.u32 [%0], {%1, %2, %3, %4};"
                             ::"r"(stage + (i >> 2) * 16384 + (i & 3) * 512 + lane * 16),
                               "r"(pack_bf16(s[8 * i], s[8 * i + 1])), "r"(pack_bf16(s[8 * i + 2], s[8 * i + 3])),
                               "r"(pack_bf16(s[8 * i + 4], s[8 * i + 5])), "r"(pack_bf16(s[8 * i + 6], s[8 * i + 7])) : "memory");
        }
        a[0] = a[1] = 1.f;
        if (nt > 1) {
            start_scores();
            const uint32_t v_full = bar_full + 8 * r.slot, v_phase = r.phase, dv = dv0 + r.slot * (kSlotBytes >> 4);
            if (deep) r.next();
            const bool early = deep && wg_count(mbar_test(v_full, v_phase)) == 128;
            if (early) {
                wg_fence();
                issue_pv(o, p, dv);
                wg_commit();
                if (wg == 0) asm volatile("bar.arrive 6, 256;" ::: "memory");
                wg_wait<1>();
            } else {
                if (wg == 0) asm volatile("bar.arrive 6, 256;" ::: "memory");
                wg_wait<0>();
            }
            pin(s);
            pin(qf);
            softmax_tile<false>(s, m, l, a, 0, lane);
#pragma unroll
            for (int i = 0; i < 32; i++) qf[i] = pack_bf16(s[2 * i], s[2 * i + 1]);
            pin(qf);
            if (deep && !early) {
                mbar_wait(v_full, v_phase);
                wg_fence();
                issue_pv(o, p, dv);
                wg_commit();
            }
        } else {
#pragma unroll
            for (int i = 0; i < 32; i++) qf[i] = p[i];
        }

        l[0] += __shfl_xor_sync(0xffffffffu, l[0], 1);
        l[1] += __shfl_xor_sync(0xffffffffu, l[1], 1);
        l[0] += __shfl_xor_sync(0xffffffffu, l[0], 2);
        l[1] += __shfl_xor_sync(0xffffffffu, l[1], 2);
        const float inv0 = rcp(l[0]), inv1 = rcp(l[1]);
        const float fa0 = a[0] * inv0, fa1 = a[1] * inv1;
        const int mi = lane >> 3;
        uint32_t st_addr[4], ld_addr[2], fin_addr[2];
#pragma unroll
        for (int j = 0; j < 4; j++) st_addr[j] = stage + (lane & 15) * 128 + (((2 * j + (lane >> 4)) ^ (lane & 7)) << 4);
#pragma unroll
        for (int j = 0; j < 2; j++) ld_addr[j] = stage + 16384 + (4 * j + mi) * 128 + (((lane & 7) ^ (4 * j + mi)) << 4);
#pragma unroll
        for (int j = 0; j < 2; j++) fin_addr[j] = stage + 16384 + (lane & 7) * 128 + (((4 * j + mi) ^ (lane & 7)) << 4);
        uint4* dst = reinterpret_cast<uint4*>(out) + (size_t)(bh * kRows + warp * 16 + mi) * 16 + 8 + (lane & 7);
        pin(st_addr);
        pin(ld_addr);
        pin(fin_addr);
        asm volatile("" : "+l"(dst));
        const uint32_t dv_lo = dv0 + r.slot * (kSlotBytes >> 4);
        r.next();
        const uint32_t dv_hi = dv0 + r.slot * (kSlotBytes >> 4);
        sched_fence(inv0 + inv1);
        wg_wait<0>();
        pin(o);
        pin(p);
        if (deep) {
#pragma unroll
            for (int i = 0; i < 8; i++)
                asm volatile("ld.shared.v4.u32 {%0, %1, %2, %3}, [%4];"
                             : "=r"(p[4 * i]), "=r"(p[4 * i + 1]), "=r"(p[4 * i + 2]), "=r"(p[4 * i + 3])
                             : "r"(stage + (i >> 2) * 16384 + (i & 3) * 512 + lane * 16) : "memory");
        } else {
            mbar_wait(bar_empty + 8 * spare, spare_free);
        }
        float lo[32], hi[32], x[32], y[32];
#pragma unroll
        for (int i = 0; i < 32; i++) lo[i] = o[i] * a_parked[(i >> 1) & 1];
        pin(lo);
        pin(p);
        tail_units<0, 2>(lo, p, dv_lo, bar_tail);
#pragma unroll
        for (int i = 0; i < 32; i++) hi[i] = o[32 + i] * a_parked[(i >> 1) & 1];
        pin(hi);
        tail_units<2, 4>(lo, p, dv_lo, bar_tail);
        tail_units<0, 4, true>(x, qf, dv_lo + (16384 >> 4), bar_tail + 32);
        static_assert(kHeldUnits >= 1 && kHeldUnits <= 3, "the first unit of y is not held back");
        auto stage_half = [&](const float (&u)[32], const float (&v)[32], const int half) {
#pragma unroll
            for (int j = 0; j < 4; j++)
                stsm4(st_addr[j] + half * 16384,
                      pack_bf16(fmaf(v[8 * j], inv0, u[8 * j]), fmaf(v[8 * j + 1], inv0, u[8 * j + 1])),
                      pack_bf16(fmaf(v[8 * j + 2], inv1, u[8 * j + 2]), fmaf(v[8 * j + 3], inv1, u[8 * j + 3])),
                      pack_bf16(fmaf(v[8 * j + 4], inv0, u[8 * j + 4]), fmaf(v[8 * j + 5], inv0, u[8 * j + 5])),
                      pack_bf16(fmaf(v[8 * j + 6], inv1, u[8 * j + 6]), fmaf(v[8 * j + 7], inv1, u[8 * j + 7])));
        };
        wg_wait<4>();
        pin(lo);
#pragma unroll
        for (int i = 0; i < 32; i++) lo[i] *= (i & 2) ? fa1 : fa0;
        pin(lo);
        sched_fence(inv0);
        wg_wait<0>();
        pin(x);
        stage_half(lo, x, 0);
        asm volatile("fence.proxy.async.shared::cta;" ::: "memory");
        __syncwarp();
        if (lane == 0) mbar_arrive(bar_staged + 8 * wg);
        tail_units<0, 4>(hi, p, dv_hi, bar_tail + 64);
        tail_units<0, 4 - kHeldUnits, true>(y, qf, dv_hi + (16384 >> 4), bar_tail + 96);
        asm volatile("{ .reg .pred p; setp.ne.u32 p, %0, 0; @p bar.sync 8, 256; }" ::"r"(wg) : "memory");
        tail_units<4 - kHeldUnits, 4>(y, qf, dv_hi + (16384 >> 4), bar_tail + 96);
        asm volatile("{ .reg .pred p; setp.eq.u32 p, %0, 0; @p bar.arrive 8, 256; }" ::"r"(wg) : "memory");
        wg_wait<4>();
        pin(hi);
#pragma unroll
        for (int i = 0; i < 32; i++) hi[i] *= (i & 2) ? fa1 : fa0;
        pin(hi);
        sched_fence(inv0);
        wg_wait<0>();
        pin(y);
#pragma unroll
        for (int e = 0; e < 2; e++) {
            const float inv = e ? inv1 : inv0;
#pragma unroll
            for (int j = 0; j < 2; j++) {
                uint32_t wd[4];
#pragma unroll
                for (int k = 0; k < 4; k++) {
                    const int i = 16 * j + 4 * k + 2 * e;
                    wd[k] = pack_bf16(fmaf(y[i], inv, hi[i]), fmaf(y[i + 1], inv, hi[i + 1]));
                }
                stsm4(fin_addr[j] + e * 1024, wd[0], wd[1], wd[2], wd[3]);
            }
            __syncwarp();
#pragma unroll
            for (int i = 2 * e; i < 2 * e + 2; i++) {
                uint4 v;
                asm volatile("ld.shared.v4.u32 {%0, %1, %2, %3}, [%4];"
                             : "=r"(v.x), "=r"(v.y), "=r"(v.z), "=r"(v.w) : "r"(ld_addr[i & 1] + (i >> 1) * 1024) : "memory");
                asm volatile("st.global.v4.u32 [%0], {%1, %2, %3, %4};"
                             ::"l"(dst + i * 64), "r"(v.x), "r"(v.y), "r"(v.z), "r"(v.w) : "memory");
            }
        }
    }
}

typedef CUresult (*EncodeFn)(CUtensorMap*, CUtensorMapDataType, cuuint32_t, void*, const cuuint64_t*, const cuuint64_t*,
                             const cuuint32_t*, const cuuint32_t*, CUtensorMapInterleave, CUtensorMapSwizzle,
                             CUtensorMapL2promotion, CUtensorMapFloatOOBfill);

void encode_rows(EncodeFn enc, CUtensorMap* m, void* base, int box_rows) {
    cuuint64_t dims[2] = {(cuuint64_t)kD, (cuuint64_t)kGrid * kRows};
    cuuint64_t strides[1] = {(cuuint64_t)kD * 2};
    cuuint32_t box[2] = {64, (cuuint32_t)box_rows};
    cuuint32_t es[2] = {1, 1};
    enc(m, CU_TENSOR_MAP_DATA_TYPE_BFLOAT16, 2, base, dims, strides, box, es, CU_TENSOR_MAP_INTERLEAVE_NONE,
        CU_TENSOR_MAP_SWIZZLE_128B, CU_TENSOR_MAP_L2_PROMOTION_L2_128B, CU_TENSOR_MAP_FLOAT_OOB_FILL_NONE);
}

void encode_cache(EncodeFn enc, CUtensorMap* m, void* base, int num_phys, int rows, int halves, int groups) {
    cuuint64_t dims[5] = {64, 8, 2, (cuuint64_t)num_phys * 2, (cuuint64_t)kHkv};
    cuuint64_t strides[4] = {(cuuint64_t)kHkv * kD * 2, 128, (cuuint64_t)8 * kHkv * kD * 2, (cuuint64_t)kD * 2};
    cuuint32_t box[5] = {64, (cuuint32_t)rows, (cuuint32_t)halves, (cuuint32_t)groups, 1};
    cuuint32_t es[5] = {1, 1, 1, 1, 1};
    enc(m, CU_TENSOR_MAP_DATA_TYPE_BFLOAT16, 5, base, dims, strides, box, es, CU_TENSOR_MAP_INTERLEAVE_NONE,
        CU_TENSOR_MAP_SWIZZLE_128B, CU_TENSOR_MAP_L2_PROMOTION_L2_128B, CU_TENSOR_MAP_FLOAT_OOB_FILL_NONE);
}

void encode_window(EncodeFn enc, CUtensorMap* m, void* base, int num_phys) {
    const cuuint64_t token = (cuuint64_t)kHkv * kD * 2;
    cuuint64_t dims[5] = {64, 8, 2, (cuuint64_t)num_phys * kPage - 7, (cuuint64_t)kHkv};
    cuuint64_t strides[4] = {token, 128, token, (cuuint64_t)kD * 2};
    cuuint32_t box[5] = {64, 8, 2, 1, 1};
    cuuint32_t es[5] = {1, 1, 1, 1, 1};
    enc(m, CU_TENSOR_MAP_DATA_TYPE_BFLOAT16, 5, base, dims, strides, box, es, CU_TENSOR_MAP_INTERLEAVE_NONE,
        CU_TENSOR_MAP_SWIZZLE_128B, CU_TENSOR_MAP_L2_PROMOTION_L2_128B, CU_TENSOR_MAP_FLOAT_OOB_FILL_NONE);
}

}

extern "C" void kernel_launch(void* const* d_in, const int* in_sizes, int n_in, void* d_out, int out_size) {
    (void)n_in;
    (void)out_size;
    void* fn = nullptr;
    cudaDriverEntryPointQueryResult qr;
    cudaGetDriverEntryPoint("cuTensorMapEncodeTiled", &fn, cudaEnableDefault, &qr);
    EncodeFn enc = (EncodeFn)fn;
    const int num_phys = in_sizes[1] / (kPage * kHkv * kD);
    CUtensorMap mq, mk, mv, mvh, mo, mkp, mvp;
    encode_rows(enc, &mq, d_in[0], kRows);
    encode_rows(enc, &mo, d_out, 64);
    encode_cache(enc, &mk, d_in[1], num_phys, 8, 2, 2);
    encode_cache(enc, &mv, d_in[2], num_phys, 8, 2, 2);
    encode_cache(enc, &mvh, d_in[2], num_phys, 8, 1, 2);
    encode_window(enc, &mkp, d_in[1], num_phys);
    encode_window(enc, &mvp, d_in[2], num_phys);
    cudaFuncSetAttribute(paged_attn_kernel, cudaFuncAttributeMaxDynamicSharedMemorySize, kSmemBytes);
    paged_attn_kernel<<<kGrid, kThreads, kSmemBytes>>>((const __nv_bfloat16*)d_in[0], (const int*)d_in[3], (const int*)d_in[4],
                                                       (__nv_bfloat16*)d_out, num_phys, mq, mk, mv, mvh, mo, mkp, mvp);
}
```

```cpp
#include <cuda_runtime.h>
#include <cuda_bf16.h>
#include <cuda.h>
#include <stdint.h>

namespace {

constexpr int kB = 16, kHkv = 8, kD = 128, kPage = 16, kMaxPages = 256;
constexpr int kRows = 128;
constexpr int kTilePages = 8;
constexpr int kSlotBytes = 32768, kPageBytes = 4096;
constexpr int kNumSlots = 7;
constexpr int kTailUnits = 16;
constexpr int kGrid = kB * kHkv;
constexpr int kThreads = 384;
constexpr int kAhead = 18;
constexpr int kTaper4 = 17, kTaperFrom = 64, kTaperTo = 32;
constexpr int kAheadStart = 6, kFade = 128;
constexpr int kEndPages = 64;
constexpr int kLead = 5;
constexpr int kTau = 4096;
constexpr int kHeadPages = 8;
constexpr int kShared = 3;
constexpr int kSendDelay = 380;
constexpr int kHeldUnits = 3;
constexpr int kBitmapWords = 132;
constexpr uint32_t kUnit = 1u << 25;
static_assert((unsigned long long)kUnit * kGrid == (1ull << 32), "counter must wrap to zero after every launch");

constexpr int kOffRing = 0;
constexpr int kOffMisc = kOffRing + kNumSlots * kSlotBytes;
constexpr int kOffPages = kOffMisc;
constexpr int kOffBitmap = kOffPages + kMaxPages * 4;
constexpr int kOffCounts = kOffBitmap + kBitmapWords * 4;
constexpr int kOffBars = kOffCounts + 256;
constexpr int kOffFlags = kOffBars + (2 * kNumSlots + kTailUnits + 4) * 8;
constexpr int kFlagWords = 6;
constexpr int kSmemBytes = kOffFlags + kFlagWords * 4;
static_assert(kSmemBytes <= 232448 && kOffFlags % 16 == 0, "shared memory budget");

__device__ uint32_t g_progress;

__device__ __forceinline__ uint32_t smem_u32(const void* p) { return (uint32_t)__cvta_generic_to_shared(p); }
__device__ __forceinline__ void mbar_init(uint32_t bar, uint32_t cnt) {
    asm volatile("mbarrier.init.shared::cta.b64 [%0], %1;" ::"r"(bar), "r"(cnt) : "memory");
}
__device__ __forceinline__ void mbar_expect_tx(uint32_t bar, uint32_t bytes) {
    asm volatile("mbarrier.arrive.expect_tx.shared::cta.b64 _, [%0], %1;" ::"r"(bar), "r"(bytes) : "memory");
}
__device__ __forceinline__ void mbar_arrive(uint32_t bar) {
    asm volatile("mbarrier.arrive.shared::cta.b64 _, [%0];" ::"r"(bar) : "memory");
}
__device__ __forceinline__ void mbar_wait(uint32_t bar, uint32_t parity) {
    asm volatile(
        "{ .reg .pred p; .reg .u32 c;\n"
        "mov.u32 c, 0;\n"
        "WAIT_%=: mbarrier.try_wait.parity.shared::cta.b64 p, [%0], %1;\n"
        "@p bra.uni DONE_%=;\n"
        "add.u32 c, c, 1;\n"
        "setp.gt.u32 p, c, 0x1000000;\n"
        "@p trap;\n"
        "bra.uni WAIT_%=;\n"
        "DONE_%=: }"
        ::"r"(bar), "r"(parity) : "memory");
}
__device__ __forceinline__ uint32_t mbar_test(uint32_t bar, uint32_t parity) {
    uint32_t ok;
    asm volatile("{ .reg .pred p; mbarrier.test_wait.parity.shared::cta.b64 p, [%1], %2; selp.u32 %0, 1, 0, p; }"
                 : "=r"(ok) : "r"(bar), "r"(parity) : "memory");
    return ok;
}
__device__ __forceinline__ uint32_t clock_u32() {
    uint32_t c;
    asm volatile("mov.u32 %0, %%clock;" : "=r"(c));
    return c;
}
__device__ __forceinline__ uint32_t clock_after(uint32_t dep) {
    uint32_t c;
    asm volatile("{ .reg .pred p; setp.eq.u32 p, %1, 0xffffffff; mov.u32 %0, 0; @!p mov.u32 %0, %%clock; }" : "=r"(c) : "r"(dep));
    return c;
}
__device__ __forceinline__ void trap_if(bool c) {
    asm volatile("{ .reg .pred p; setp.ne.b32 p, %0, 0; @p trap; }" ::"r"((int)c));
}
__device__ __forceinline__ void sched_fence(float x) {
    asm volatile(
        "{ .reg .pred p; .reg .u32 t;\n"
        "setp.lt.f32 p, %0, 0f00000000;\n"
        "@!p bra D_%=;\n"
        "F_%=: mov.u32 t, %%clock;\n"
        "setp.eq.u32 p, t, 0;\n"
        "@p bra F_%=;\n"
        "D_%=: }" ::"f"(x) : "memory");
}
__device__ __forceinline__ uint32_t lds_volatile(uint32_t a) {
    uint32_t v;
    asm volatile("ld.volatile.shared.u32 %0, [%1];" : "=r"(v) : "r"(a) : "memory");
    return v;
}
__device__ __forceinline__ void sts_volatile(uint32_t a, uint32_t v) {
    asm volatile("st.volatile.shared.u32 [%0], %1;" ::"r"(a), "r"(v) : "memory");
}
__device__ __forceinline__ void tma_load_page(uint32_t dst, const CUtensorMap* map, uint32_t bar, int half, int row8, int head, uint64_t pol, int row = 0) {
    asm volatile(
        "cp.async.bulk.tensor.5d.shared::cluster.global.mbarrier::complete_tx::bytes.L2::cache_hint "
        "[%0], [%1, {%3, %8, %7, %4, %5}], [%2], %6;"
        ::"r"(dst), "l"(map), "r"(bar), "r"(0), "r"(row8), "r"(head), "l"(pol), "r"(half), "r"(row) : "memory");
}
__device__ __forceinline__ void tma_load_2d(uint32_t dst, const CUtensorMap* map, uint32_t bar, int c0, int c1) {
    asm volatile(
        "cp.async.bulk.tensor.2d.shared::cluster.global.mbarrier::complete_tx::bytes [%0], [%1, {%3, %4}], [%2];"
        ::"r"(dst), "l"(map), "r"(bar), "r"(c0), "r"(c1) : "memory");
}
__device__ __forceinline__ void tma_store_2d(const CUtensorMap* map, uint32_t src, int c0, int c1) {
    asm volatile("cp.async.bulk.tensor.2d.global.shared::cta.bulk_group [%0, {%2, %3}], [%1];"
                 ::"l"(map), "r"(src), "r"(c0), "r"(c1) : "memory");
}
__device__ __forceinline__ float ex2(float x) {
    float y;
    asm("ex2.approx.ftz.f32 %0, %1;" : "=f"(y) : "f"(x));
    return y;
}
__device__ __forceinline__ float rcp(float x) {
    float y;
    asm("rcp.approx.ftz.f32 %0, %1;" : "=f"(y) : "f"(x));
    return y;
}
__device__ __forceinline__ uint32_t pack_bf16(float lo, float hi) {
    uint32_t r;
    asm("cvt.rn.bf16x2.f32 %0, %1, %2;" : "=r"(r) : "f"(hi), "f"(lo));
    return r;
}
__device__ __forceinline__ uint32_t desc_lo(uint32_t addr, uint32_t lbo) { return ((addr & 0x3FFFF) >> 4) | ((lbo >> 4) << 16); }
constexpr uint32_t kDescHi = (2048 >> 4) | (1u << 30), kDescHiDense = (1024 >> 4) | (1u << 30);
__device__ __forceinline__ void wg_fence() { asm volatile("wgmma.fence.sync.aligned;" ::: "memory"); }
__device__ __forceinline__ void wg_commit() { asm volatile("wgmma.commit_group.sync.aligned;" ::: "memory"); }
template <int N> __device__ __forceinline__ void wg_wait() { asm volatile("wgmma.wait_group.sync.aligned %0;" ::"n"(N) : "memory"); }
template <int N> __device__ __forceinline__ void wg_wait_release(uint32_t bar, int lane) {
    asm volatile(
        "{ .reg .pred p; setp.eq.s32 p, %2, 0;\n"
        "wgmma.wait_group.sync.aligned %0;\n"
        "@p mbarrier.arrive.shared::cta.b64 _, [%1]; }" ::"n"(N), "r"(bar), "r"(lane) : "memory");
}
template <int N> __device__ __forceinline__ void pin(float (&r)[N]) {
#pragma unroll
    for (int i = 0; i < N; i++) asm volatile("" : "+f"(r[i])::"memory");
}
template <int N> __device__ __forceinline__ void pin(uint32_t (&r)[N]) {
#pragma unroll
    for (int i = 0; i < N; i++) asm volatile("" : "+r"(r[i])::"memory");
}

#define ACC_REGS                                                                        \
    "{%0, %1, %2, %3, %4, %5, %6, %7, %8, %9, %10, %11, %12, %13, %14, %15, "           \
    "%16, %17, %18, %19, %20, %21, %22, %23, %24, %25, %26, %27, %28, %29, %30, %31, "  \
    "%32, %33, %34, %35, %36, %37, %38, %39, %40, %41, %42, %43, %44, %45, %46, %47, "  \
    "%48, %49, %50, %51, %52, %53, %54, %55, %56, %57, %58, %59, %60, %61, %62, %63}"
#define ACC8(d, i) "+f"(d[i]), "+f"(d[i + 1]), "+f"(d[i + 2]), "+f"(d[i + 3]), "+f"(d[i + 4]), "+f"(d[i + 5]), "+f"(d[i + 6]), "+f"(d[i + 7])
#define ACC_OPS(d) ACC8(d, 0), ACC8(d, 8), ACC8(d, 16), ACC8(d, 24), ACC8(d, 32), ACC8(d, 40), ACC8(d, 48), ACC8(d, 56)

template <int kAcc, int kTrans> __device__ __forceinline__ void mma(float (&d)[64], const uint32_t* a, uint32_t db) {
    asm volatile(
        "{ .reg .b64 db; mov.b64 db, {%68, %69};\n"
        "wgmma.mma_async.sync.aligned.m64n128k16.f32.bf16.bf16 " ACC_REGS ", {%64, %65, %66, %67}, db, %70, 1, 1, %71; }"
        : ACC_OPS(d) : "r"(a[0]), "r"(a[1]), "r"(a[2]), "r"(a[3]), "r"(db), "n"(kDescHi), "n"(kAcc), "n"(kTrans));
}
#define HALF_MMA(acc)                                                                                             \
    "{ .reg .b64 db; mov.b64 db, {%36, %37};\n"                                                                   \
    "wgmma.mma_async.sync.aligned.m64n64k16.f32.bf16.bf16 "                                                       \
    "{%0, %1, %2, %3, %4, %5, %6, %7, %8, %9, %10, %11, %12, %13, %14, %15, "                                     \
    "%16, %17, %18, %19, %20, %21, %22, %23, %24, %25, %26, %27, %28, %29, %30, %31}, {%32, %33, %34, %35}, db, " \
    acc ", 1, 1, 1; }"
#define OUT8(d, i) "=f"(d[i]), "=f"(d[i + 1]), "=f"(d[i + 2]), "=f"(d[i + 3]), "=f"(d[i + 4]), "=f"(d[i + 5]), "=f"(d[i + 6]), "=f"(d[i + 7])
template <bool kAcc> __device__ __forceinline__ void mma_half(float (&d)[32], const uint32_t* a, uint32_t db) {
    if (kAcc)
        asm volatile(HALF_MMA("1") : ACC8(d, 0), ACC8(d, 8), ACC8(d, 16), ACC8(d, 24)
                     : "r"(a[0]), "r"(a[1]), "r"(a[2]), "r"(a[3]), "r"(db), "n"(kDescHiDense));
    else
        asm volatile(HALF_MMA("0") : OUT8(d, 0), OUT8(d, 8), OUT8(d, 16), OUT8(d, 24)
                     : "r"(a[0]), "r"(a[1]), "r"(a[2]), "r"(a[3]), "r"(db), "n"(kDescHiDense));
}
template <int J0, int J1, bool kFresh = false>
__device__ __forceinline__ void tail_units(float (&d)[32], const uint32_t (&p)[32], uint32_t db, uint32_t bars) {
#pragma unroll
    for (int j = J0; j < J1; j++) {
        mbar_wait(bars + 8 * j, 0);
        wg_fence();
        if (kFresh && j == 0) mma_half<false>(d, p + 8 * j, db + j * (kPageBytes >> 4));
        else mma_half<true>(d, p + 8 * j, db + j * (kPageBytes >> 4));
        mma_half<true>(d, p + 8 * j + 4, db + j * (kPageBytes >> 4) + (2048 >> 4));
        wg_commit();
    }
}
__device__ __forceinline__ void stsm4(uint32_t addr, uint32_t r0, uint32_t r1, uint32_t r2, uint32_t r3) {
    asm volatile("stmatrix.sync.aligned.m8n8.x4.shared.b16 [%0], {%1, %2, %3, %4};"
                 ::"r"(addr), "r"(r0), "r"(r1), "r"(r2), "r"(r3) : "memory");
}
__device__ __forceinline__ void scale_rows(float (&o)[64], float f0, float f1) {
#pragma unroll
    for (int j = 0; j < 16; j++) {
        o[4 * j] *= f0;
        o[4 * j + 1] *= f0;
        o[4 * j + 2] *= f1;
        o[4 * j + 3] *= f1;
    }
}
__device__ __forceinline__ void issue_qk(float (&s)[64], const uint32_t (&qf)[32], uint32_t dk) {
    mma<0, 0>(s, qf, dk);
#pragma unroll
    for (int k = 1; k < 8; k++) mma<1, 0>(s, qf + 4 * k, dk + (((k >> 2) * 1024 + (k & 3) * 32) >> 4));
}
__device__ __forceinline__ void issue_pv(float (&o)[64], const uint32_t (&p)[32], uint32_t dv) {
#pragma unroll
    for (int k = 0; k < 8; k++) mma<1, 1>(o, p + 4 * k, dv + k * (kPageBytes >> 4));
}

__device__ __forceinline__ void item_of(int i, int nt, int& tile, int& is_v) {
    if (nt >= 3 && (i >> 1) == nt - 2) i ^= 1;
    is_v = (i != 0) & ~i & 1;
    tile = is_v ? (i >> 1) - 1 : (i + 1) >> 1;
}

struct Pace {
    int knee, total;
    uint32_t step, end_step;
    __device__ __forceinline__ Pace(int np, int all_pages) {
        total = 2 * np;
        end_step = (uint32_t)((float)kUnit * ((float)kB / (float)(2 * all_pages)));
        const bool bend = total > 2 * kEndPages && all_pages * 2 > 2 * kEndPages * kB;
        knee = bend ? total - kEndPages : total;
        step = (kUnit - (uint32_t)(total - knee) * end_step) / (uint32_t)knee;
    }
    __device__ __forceinline__ uint32_t at(int c) const {
        return c < knee ? (uint32_t)c * step : kUnit - (uint32_t)(total - c) * end_step;
    }
};

struct Seq {
    bool flat;
    int cl, np, nt;
    int first_pages;
    int nitems;
    int valid;
    bool trim;
    __device__ __forceinline__ explicit Seq(int len) {
        flat = len <= 0;
        cl = flat ? kMaxPages * kPage : min(len, kMaxPages * kPage);
        np = (cl + kPage - 1) >> 4;
        nt = (np + kTilePages - 1) >> 3;
        first_pages = np - (nt - 1) * kTilePages;
        nitems = max(2 * nt, 3);
        valid = cl - (np - 1) * kPage;
        trim = nt >= 4;
    }
};

struct Ring {
    int slot = 0;
    uint32_t phase = 0;
    __device__ __forceinline__ void next() {
        if (++slot == kNumSlots) { slot = 0; phase ^= 1; }
    }
};

template <bool kFirst>
__device__ __forceinline__ void softmax_tile(float (&s)[64], float (&m)[2], float (&l)[2], float (&a)[2], int ncols, int lane) {
    constexpr float c = 0.08838834764831845f * 1.4426950408889634f;
    if (kFirst) {
        const int lim = ncols - 2 * (lane & 3);
#pragma unroll
        for (int i = 0; i < 64; i++) s[i] = (8 * (i >> 2) + (i & 1) < lim) ? s[i] : -INFINITY;
    }
    float mq[2][4];
#pragma unroll
    for (int g = 0; g < 4; g++) {
#pragma unroll
        for (int e = 0; e < 2; e++) {
            mq[e][g] = fmaxf(s[4 * g + 2 * e], s[4 * g + 2 * e + 1]);
#pragma unroll
            for (int j = g + 4; j < 16; j += 4) mq[e][g] = fmaxf(fmaxf(mq[e][g], s[4 * j + 2 * e]), s[4 * j + 2 * e + 1]);
        }
    }
    float mx0 = fmaxf(fmaxf(mq[0][0], mq[0][1]), fmaxf(mq[0][2], mq[0][3]));
    float mx1 = fmaxf(fmaxf(mq[1][0], mq[1][1]), fmaxf(mq[1][2], mq[1][3]));
    mx0 = fmaxf(mx0, __shfl_xor_sync(0xffffffffu, mx0, 1));
    mx1 = fmaxf(mx1, __shfl_xor_sync(0xffffffffu, mx1, 1));
    mx0 = fmaxf(mx0, __shfl_xor_sync(0xffffffffu, mx0, 2));
    mx1 = fmaxf(mx1, __shfl_xor_sync(0xffffffffu, mx1, 2));
    if (!kFirst) {
        mx0 = fmaxf(mx0, m[0]);
        mx1 = fmaxf(mx1, m[1]);
    }
    const float b0 = __fmul_rn(mx0, -c), b1 = __fmul_rn(mx1, -c);
    if (!kFirst) {
        a[0] = ex2(__fadd_rn(__fmul_rn(m[0], c), b0));
        a[1] = ex2(__fadd_rn(__fmul_rn(m[1], c), b1));
    }
    m[0] = mx0;
    m[1] = mx1;
    float r0 = 0.f, r1 = 0.f;
#pragma unroll
    for (int j = 0; j < 16; j++) {
        s[4 * j] = ex2(fmaf(s[4 * j], c, b0));
        s[4 * j + 1] = ex2(fmaf(s[4 * j + 1], c, b0));
        s[4 * j + 2] = ex2(fmaf(s[4 * j + 2], c, b1));
        s[4 * j + 3] = ex2(fmaf(s[4 * j + 3], c, b1));
        r0 += s[4 * j] + s[4 * j + 1];
        r1 += s[4 * j + 2] + s[4 * j + 3];
    }
    if (kFirst) { l[0] = r0; l[1] = r1; }
    else { l[0] = fmaf(l[0], a[0], r0); l[1] = fmaf(l[1], a[1], r1); }
}

__global__ void __launch_bounds__(kThreads, 1)
paged_attn_kernel(const __nv_bfloat16* __restrict__ q, const int* __restrict__ block_table, const int* __restrict__ context_lens,
                  __nv_bfloat16* __restrict__ out, int num_phys,
                  const __grid_constant__ CUtensorMap map_q, const __grid_constant__ CUtensorMap map_k,
                  const __grid_constant__ CUtensorMap map_v, const __grid_constant__ CUtensorMap map_vh,
                  const __grid_constant__ CUtensorMap map_o, const __grid_constant__ CUtensorMap map_kp,
                  const __grid_constant__ CUtensorMap map_vp) {
    extern __shared__ __align__(1024) unsigned char sptr[];
    const uint32_t sbase = smem_u32(sptr);
    const uint32_t bar_full = sbase + kOffBars, bar_empty = bar_full + 8 * kNumSlots, bar_tail = bar_empty + 8 * kNumSlots;
    const uint32_t bar_q = bar_tail + 8 * kTailUnits, bar_qfree = bar_q + 8, bar_staged = bar_qfree + 8;
    const uint32_t s_q = sbase + kOffRing + (kNumSlots - 1) * kSlotBytes;
    const uint32_t s_prog = sbase + kOffFlags, s_rate = s_prog + 8, s_done = s_prog + 12, s_stop = s_prog + 16, s_zero = s_prog + 20;
    int* s_pages = reinterpret_cast<int*>(sptr + kOffPages);
    uint32_t* s_bitmap = reinterpret_cast<uint32_t*>(sptr + kOffBitmap);

    const int tid = threadIdx.x, lane = tid & 31;
    const int bh = blockIdx.x, b = bh >> 3, h = bh & 7;

    int cl_lane, my_page;
    asm volatile(
        "{ .reg .pred r, p; .reg .b64 a; .reg .u32 t;\n"
        "setp.ge.u32 r, %6, 256;\n"
        "mad.wide.u32 a, %6, 128, %2;\n"
        "@r prefetch.global.L2 [a + -16384];\n"
        "@r bra P_%=;\n"
        "mad.wide.u32 a, %6, 4, %3;\n"
        "ld.global.nc.s32 %0, [a];\n"
        "ld.global.nc.s32 %1, [%4];\n"
        "mad.wide.u32 a, %6, 64, %2;\n"
        "prefetch.global.L2 [a];\n"
        "setp.ne.u32 p, %6, 999;\n"
        "@p bra E_%=;\n"
        "F_%=: mov.u32 t, %%clock; setp.eq.u32 p, t, 0; @p bra F_%=;\n"
        "bra E_%=;\n"
        "P_%=: and.b32 t, %6, 15;\n"
        "mad.wide.u32 a, t, 4, %5;\n"
        "ld.global.nc.s32 %1, [a];\n"
        "mov.u32 %0, 0;\n"
        "setp.ne.u32 p, %6, 999;\n"
        "@p bra E_%=;\n"
        "G_%=: mov.u32 t, %%clock; setp.eq.u32 p, t, 0; @p bra G_%=;\n"
        "E_%=: }"
        : "=&r"(my_page), "=&r"(cl_lane)
        : "l"(q + (size_t)bh * kRows * kD), "l"(block_table + (size_t)b * kMaxPages), "l"(context_lens + b), "l"(context_lens), "r"(tid)
        : "memory");
    const int warp = __shfl_sync(0xffffffffu, tid >> 5, 0);
    uint64_t pol;
    asm("createpolicy.fractional.L2::evict_first.b64 %0, 1.0;" : "=l"(pol));

    if (warp == 8) {
        if (lane == 0) {
            mbar_init(bar_q, 1);
            asm volatile("fence.mbarrier_init.release.cluster;" ::: "memory");
            mbar_expect_tx(bar_q, 32768);
            tma_load_2d(s_q, &map_q, bar_q, 0, bh * kRows);
            tma_load_2d(s_q + 16384, &map_q, bar_q, 64, bh * kRows);
        }
    } else if (warp == 9) {
        if (lane == 0) {
            for (int i = 0; i < kNumSlots; i++) mbar_init(bar_full + 8 * i, 1);
            asm volatile("fence.mbarrier_init.release.cluster;" ::: "memory");
        }
    } else if (warp == 10) {
        if (lane == 0) {
            asm volatile("prefetch.tensormap [%0];" ::"l"(&map_k) : "memory");
            asm volatile("prefetch.tensormap [%0];" ::"l"(&map_v) : "memory");
            asm volatile("prefetch.tensormap [%0];" ::"l"(&map_kp) : "memory");
            asm volatile("prefetch.tensormap [%0];" ::"l"(&map_vp) : "memory");
        }
    } else if (warp == 11) {
        trap_if(sbase & 1023);
        if (lane < kFlagWords) sts_volatile(s_prog + 4 * lane, 0);
        if (lane == 0) {
            for (int i = 0; i < kNumSlots; i++) mbar_init(bar_empty + 8 * i, 9);
            mbar_init(bar_qfree, 8);
            mbar_init(bar_staged, 4);
            mbar_init(bar_staged + 8, 4);
        }
    } else if (tid < kBitmapWords) {
        s_bitmap[tid] = 0;
    }
    __syncthreads();
    if (warp == 9) {
        if (lane == 0) {
            for (int i = 0; i < kTailUnits; i++) mbar_init(bar_tail + 8 * i, 1);
            for (int i = 0; i < kTailUnits; i++) mbar_expect_tx(bar_tail + 8 * i, kPageBytes);
            asm volatile("fence.mbarrier_init.release.cluster;" ::: "memory");
        }
        __syncwarp();
        asm volatile("bar.arrive 2, 320;" ::: "memory");
        asm volatile("bar.arrive 7, 320;" ::: "memory");
    }

    if (warp >= 8) {
        asm volatile("setmaxnreg.dec.sync.aligned.u32 40;");
        const Seq sq(__shfl_sync(0xffffffffu, cl_lane, b + lds_volatile(s_zero)));
        const bool flat = sq.flat, side_fill = sq.trim, partial = sq.trim && sq.valid < kPage;
        const int np = sq.np, nt = sq.nt, first_pages = sq.first_pages, nitems = sq.nitems;
        const uint32_t tail_pages = nt >= 3 ? 0xffffu : nt == 2 ? 0xff00u | ((1u << first_pages) - 1) : ((1u << first_pages) - 1) << 8;
        const int head = sq.trim && !flat ? kHeadPages : 0;
        if (warp == 11) {
            const int slot = lane >= first_pages;
            const uint32_t dst0 = sbase + kOffRing + slot * kSlotBytes + (lane - slot * first_pages) * kPageBytes;
            uint32_t first = lane < head && !(partial && lane == first_pages - 1), dst_r = dst0, full_r = bar_full + 8 * slot;
            asm volatile("" : "+r"(first), "+r"(dst_r), "+r"(full_r));
            asm volatile("bar.sync 7, 320;" ::: "memory");
            if (first) tma_load_page(dst_r, &map_k, full_r, 0, s_pages[lane] * 2, h, pol);
            const int start = s_pages[first_pages - 1] * kPage + 8 * lane;
            const int skip = start ? 8 - min(max(sq.valid - 8 * lane, 0), 8) : 0;
            const uint32_t dst = sbase + kOffRing + (first_pages - 1) * kPageBytes + lane * 2048;
            if (partial && lane < 2) {
                tma_load_page(dst, &map_kp, bar_full, 0, start - skip, h, pol, skip);
                tma_load_page(dst + 2 * kSlotBytes, &map_vp, bar_full + 16, 0, start - skip, h, pol, skip);
            }
        }
        const int c_lane = (cl_lane <= 0) ? kMaxPages * kPage : min(cl_lane, kMaxPages * kPage);
        const int all_pages = __reduce_add_sync(0xffffffffu, (lane < kB) ? (c_lane + kPage - 1) / kPage : 0);
        const Pace pace(np, all_pages);
        if (warp == 8 || warp == 11) {
            const uint32_t ahead = (uint32_t)fminf((float)kAhead * (float)pace.end_step, (float)kUnit);
            const uint32_t taper_step = ahead / (4 * kAhead * (kTaperFrom - kTaperTo)) * kTaper4;
            const int v0_item = nt == 3 ? 3 : 2;
            Ring r;
            r.slot = warp == 8 ? 0 : kShared;
            for (int i = r.slot; i < nitems; i += (i < kShared - 1) ? 1 : 2) {
                int issued = 8 * i - (i > 0 ? 8 - first_pages : 0) - (nt >= 3 && i > v0_item ? 8 - first_pages : 0);
                if (i == nitems - 1) issued += (min(np, 16) >> 1) - 8;
                const bool tail = i >= nitems - 2;
                const int half = tail ? i - (nitems - 2) : 0;
                int tile, is_v, n, idx;
                bool pending, real;
                item_of(i, nt, tile, is_v);
                if (tail) {
                    n = (min(np, 16) + half) >> 1;
                    idx = nt >= 2 ? (nt == 2 && lane < 8 ? lane : np - 16 + lane) : lane - 8;
                    pending = lane < 16;
                    real = lane < 16 && (tail_pages >> lane & 1);
                } else {
                    n = tile ? kTilePages : first_pages;
                    idx = (tile ? first_pages + (tile - 1) * kTilePages : 0) + lane;
                    pending = lane < (is_v && !side_fill ? kTilePages : n) && !(partial && tile == 0 && lane == n - 1) &&
                              !(i < 2 && idx < head);
                    real = lane < n && (is_v || !flat);
                }
                const uint32_t full = tail ? bar_tail + 8 * (8 * half + (lane >> 1)) : bar_full + 8 * r.slot;
                if (i == kNumSlots - 1) mbar_wait(bar_qfree, 0);
                if (i == nitems - 3) {
                    asm volatile("prefetch.tensormap [%0];" ::"l"(&map_vh) : "memory");
                    asm volatile("prefetch.tensormap [%0];" ::"l"(&map_o) : "memory");
                }
                mbar_wait(bar_empty + 8 * r.slot, r.phase ^ 1);
                if (!tail && lane == 0)
                    mbar_expect_tx(full, is_v && !side_fill ? kSlotBytes : n * kPageBytes);
                __syncwarp();
                const uint32_t dst = sbase + kOffRing + r.slot * kSlotBytes + lane * (tail ? kPageBytes / 2 : kPageBytes);
                const CUtensorMap* map = tail ? &map_vh : is_v ? &map_v : &map_k;
                const int mine = issued + min((tail ? lane >> 1 : lane) + 1, n);
                const uint32_t boost = (uint32_t)max(kFade - mine, 0) * (pace.end_step / kFade * kAheadStart);
                const uint32_t taper = (uint32_t)min(max(kTaperFrom - (pace.total - mine), 0), kTaperFrom - kTaperTo) * taper_step;
                uint32_t need = pace.at(mine), room = ahead + boost - taper, dst_r = dst, full_r = full;
                asm volatile("" : "+r"(need), "+r"(room), "+r"(dst_r), "+r"(full_r), "+r"(idx));
                if (i == 0) asm volatile("bar.sync 2, 320;" ::: "memory");
                const int page = real ? s_pages[idx] : num_phys;
                uint32_t it = 0;
                do {
                    uint32_t prog, t_prog, rate, done;
                    asm volatile("ld.volatile.shared.v4.u32 {%0, %1, %2, %3}, [%4];"
                                 : "=r"(prog), "=r"(t_prog), "=r"(rate), "=r"(done) : "r"(s_prog) : "memory");
                    prog += rate * (uint32_t)min(max((int)(clock_u32() - t_prog), 0), 2048);
                    if (pending && (need <= prog + room || mine - (int)done <= kTilePages)) {
                        tma_load_page(dst_r, map, full_r, half, page * 2, h, pol);
                        pending = false;
                    }
                    trap_if(++it > (1u << 26));
                } while (__any_sync(0xffffffffu, pending));
                if (i >= kShared - 1) r.next();
                r.next();
            }
            const bool issued_last = (nitems - 1 < kShared || ((nitems - 1 - kShared) & 1)) == (warp == 8);
            if (lane == 0 && issued_last) {
                sts_volatile(s_stop, 1);
                const uint32_t stage = sbase + kOffRing + (nitems % kNumSlots) * kSlotBytes;
                const uint32_t t0 = clock_u32();
                while (clock_u32() - t0 < kSendDelay) {}
                uint32_t todo = 3, it = 0;
                while (todo) {
                    for (int g = 0; g < 2; g++) {
                        if ((todo >> g & 1) && mbar_test(bar_staged + 8 * g, 0)) {
                            tma_store_2d(&map_o, stage + g * 8192, 0, bh * kRows + g * 64);
                            todo &= ~(1u << g);
                        }
                    }
                    trap_if(++it > (1u << 26));
                }
                asm volatile("cp.async.bulk.commit_group;" ::: "memory");
                asm volatile("cp.async.bulk.wait_group.read 0;" ::: "memory");
            }
        } else if (warp == 9) {
            int done = 0;
            auto report = [&](int n) {
                const uint32_t inc = pace.at(done + n) - pace.at(done);
                done += n;
                if (lane == 0) {
                    sts_volatile(s_done, done);
                    asm volatile("red.relaxed.gpu.global.add.u32 [%0], %1;" ::"l"(&g_progress), "r"(inc) : "memory");
                }
            };
            Ring r;
            for (int i = 0; i < nitems - 2; i++) {
                int tile, is_v;
                item_of(i, nt, tile, is_v);
                mbar_wait(bar_full + 8 * r.slot, r.phase);
                if (lane == 0) mbar_arrive(bar_empty + 8 * r.slot);
                report(tile ? kTilePages : first_pages);
                r.next();
            }
            for (int i = 0; i < kTailUnits / 2; i++) mbar_wait(bar_tail + 8 * i, 0);
            report(min(np, 16) >> 1);
            mbar_wait(bar_tail + 8 * (kTailUnits / 2), 0);
            report(pace.total - done);
        } else if (warp == 10) {
            if (lane == 0) {
                uint32_t it = 0, prev = 0, t_prev = clock_u32(), t_ref = t_prev;
                float f_ref = 0.f, g = 0.f;
                const float lead = (float)kLead * (float)pace.end_step;
                while (!lds_volatile(s_stop)) {
                    uint32_t f;
                    asm volatile("ld.relaxed.gpu.global.u32 %0, [%1];" : "=r"(f) : "l"(&g_progress) : "memory");
                    f >>= 7;
                    uint32_t est = f + (f - min(prev, f));
                    prev = f;
                    const uint32_t t = clock_after(f);
                    const float ff = (float)f, dt = (float)(t - t_prev);
                    t_prev = t;
                    if (f < kUnit / 32) {
                        f_ref = ff;
                        t_ref = t;
                    }
                    if (f < kUnit / 10) {
                        g = (float)est;
                    } else {
                        const float rate = __fdividef(ff - f_ref, (float)(t - t_ref));
                        const float adv = rate * dt;
                        const float target = ff + 0.5f * adv;
                        sts_volatile(s_rate, (uint32_t)fminf(rate, 65536.f));
                        g += adv;
                        g += (target - g) * fminf(dt * (1.f / kTau), 1.f);
                        g = fminf(g, target + lead);
                        est = (uint32_t)g;
                    }
                    asm volatile("st.volatile.shared.v2.u32 [%0], {%1, %2};" ::"r"(s_prog), "r"(est), "r"(t) : "memory");
                    trap_if(++it > (1u << 22));
                }
            }
        }
    } else {
        const int len = cl_lane + (int)lds_volatile(s_zero);
        const uint32_t w = min((uint32_t)my_page >> 5, (uint32_t)kBitmapWords - 1), bit = 1u << (my_page & 31);
        const uint32_t in_sort = tid < kMaxPages - 1 && (len <= 0 || (tid + 1) * kPage < len);
        uint32_t seen, dup;
        asm volatile("{ .reg .pred p; setp.ne.u32 p, %3, 0; mov.u32 %0, 0; @p atom.shared.or.b32 %0, [%1], %2; }"
                     : "=&r"(seen) : "r"(sbase + kOffBitmap + 4 * w), "r"(bit), "r"(in_sort) : "memory");
        asm volatile("{ .reg .pred p, q; setp.ne.u32 p, %1, 0; bar.red.or.pred q, 1, 256, p; selp.u32 %0, 1, 0, q; }"
                     : "=r"(dup) : "r"((seen & bit) | (uint32_t)(num_phys > kBitmapWords * 32)) : "memory");
        const uint32_t grp = w >> 2, sub = w & 3;
        const uint4 va = reinterpret_cast<const uint4*>(s_bitmap)[lane];
        const uint4 vb = reinterpret_cast<const uint4*>(s_bitmap)[grp];
        int incl = __popc(va.x) + __popc(va.y) + __popc(va.z) + __popc(va.w);
        const uint32_t s_cnt = sbase + kOffCounts + warp * 32;
        asm volatile("st.shared.u8 [%0], %1;" ::"r"(s_cnt + lane), "r"(incl) : "memory");
        __syncwarp();
        uint32_t cw[8];
        asm volatile("ld.shared.v4.u32 {%0, %1, %2, %3}, [%4];" : "=r"(cw[0]), "=r"(cw[1]), "=r"(cw[2]), "=r"(cw[3]) : "r"(s_cnt) : "memory");
        asm volatile("ld.shared.v4.u32 {%0, %1, %2, %3}, [%4];" : "=r"(cw[4]), "=r"(cw[5]), "=r"(cw[6]), "=r"(cw[7]) : "r"(s_cnt + 16) : "memory");
        uint32_t acc0 = 0, acc1 = 0;
#pragma unroll
        for (int k = 0; k < 4; k++) {
            acc0 = __dp4a(cw[k], __funnelshift_rc(0x01010101u, 0u, max(8 * (4 * k + 4 - (int)grp), 0)), acc0);
            acc1 = __dp4a(cw[k + 4], __funnelshift_rc(0x01010101u, 0u, max(8 * (4 * k + 20 - (int)grp), 0)), acc1);
        }
        const int below = acc0 + acc1;
        const int rank = below + __popc(vb.x & (sub > 0 ? ~0u : bit - 1)) +
                         __popc(vb.y & (sub > 1 ? ~0u : sub == 1 ? bit - 1 : 0u)) +
                         __popc(vb.z & (sub > 2 ? ~0u : sub == 2 ? bit - 1 : 0u)) + __popc(vb.w & (sub == 3 ? bit - 1 : 0u));
        const Seq sq(__shfl_sync(0xffffffffu, len, 0));
        const bool flat = sq.flat, side_fill = sq.trim;
        const int cl = sq.cl, np = sq.np, nt = sq.nt, first_pages = sq.first_pages, nitems = sq.nitems;
        int pos = dup ? tid : rank;
        if (tid == np - 1) pos = first_pages - 1;
        else if (pos >= first_pages - 1) pos++;
        if (tid < np) s_pages[pos] = my_page;
        asm volatile("bar.arrive 7, 320;" ::: "memory");
        asm volatile("bar.arrive 2, 320;" ::: "memory");
        asm volatile("setmaxnreg.inc.sync.aligned.u32 232;");

        const int wg = warp >> 2;
        const int first_cols = cl - (nt - 1) * kTilePages * kPage;
        const uint32_t dk0 = desc_lo(sbase + kOffRing, 16), dv0 = desc_lo(sbase + kOffRing, 1024);

        float o[64], s[64], m[2], l[2], a[2];
        uint32_t p[32], qf[32];
        Ring r;

        if (side_fill) {
            uint4* v0 = reinterpret_cast<uint4*>(sptr + kOffRing + 2 * kSlotBytes);
            for (int pg = first_pages; pg < kTilePages; pg++) v0[pg * 256 + tid] = make_uint4(0, 0, 0, 0);
            asm volatile("fence.proxy.async.shared::cta;" ::: "memory");
        }
        mbar_wait(bar_q, 0);
        {
            const uint32_t qrow = s_q + (warp * 16 + (lane & 15)) * 128;
#pragma unroll
            for (int k = 0; k < 8; k++) {
                const uint32_t addr = qrow + (k >> 2) * 16384 + ((((k & 3) * 2 + (lane >> 4)) ^ (lane & 7)) << 4);
                asm volatile("ldmatrix.sync.aligned.m8n8.x4.shared.b16 {%0, %1, %2, %3}, [%4];"
                             : "=r"(qf[4 * k]), "=r"(qf[4 * k + 1]), "=r"(qf[4 * k + 2]), "=r"(qf[4 * k + 3]) : "r"(addr) : "memory");
            }
            if (flat) {
#pragma unroll
                for (int i = 0; i < 32; i++) qf[i] = 0u;
            }
        }
        pin(qf);
        __syncwarp();
        if (lane == 0) mbar_arrive(bar_qfree);
        mbar_wait(bar_full + 8 * r.slot, r.phase);
        wg_fence();
        issue_qk(s, qf, dk0 + r.slot * (kSlotBytes >> 4));
        wg_commit();
        wg_wait<0>();
        pin(s);
        if (lane == 0) mbar_arrive(bar_empty + 8 * r.slot);
        r.next();
        softmax_tile<true>(s, m, l, a, first_cols, lane);
#pragma unroll
        for (int i = 0; i < 32; i++) p[i] = pack_bf16(s[2 * i], s[2 * i + 1]);
#pragma unroll
        for (int i = 0; i < 64; i++) o[i] = 0.f;
        const bool deep = nt >= 3;
        const int spare = nitems % kNumSlots;
        const uint32_t spare_free = ((nitems / kNumSlots) & 1) ^ 1;
        const uint32_t stage = sbase + kOffRing + spare * kSlotBytes + warp * 2048;
        float a_parked[2] = {1.f, 1.f};
        auto wg_count = [&](bool flag) {
            uint32_t n;
            if (wg == 0)
                asm volatile("{ .reg .pred p; setp.ne.u32 p, %1, 0; bar.red.popc.u32 %0, 3, 128, p; }" : "=r"(n) : "r"((uint32_t)flag) : "memory");
            else
                asm volatile("{ .reg .pred p; setp.ne.u32 p, %1, 0; bar.red.popc.u32 %0, 4, 128, p; }" : "=r"(n) : "r"((uint32_t)flag) : "memory");
            return (int)__shfl_sync(0xffffffffu, n, 0);
        };
        if (wg == 1 && nt > 1) asm volatile("bar.arrive 5, 256;" ::: "memory");

        auto start_scores = [&]() {
            const int ks = r.slot;
            mbar_wait(bar_full + 8 * ks, r.phase);
            r.next();
            if (wg == 0) asm volatile("bar.sync 5, 256;" ::: "memory");
            else asm volatile("bar.sync 6, 256;" ::: "memory");
            pin(o);
            pin(p);
            wg_fence();
            issue_qk(s, qf, dk0 + ks * (kSlotBytes >> 4));
            wg_commit();
            return ks;
        };
        auto pass_turn = [&]() {
            if (wg == 0) asm volatile("bar.arrive 6, 256;" ::: "memory");
            else asm volatile("bar.arrive 5, 256;" ::: "memory");
        };

        for (int t = 1; t < nt - 2; t++) {
            const int ks = start_scores();
            const int vs = r.slot;
            mbar_wait(bar_full + 8 * vs, r.phase);
            r.next();
            wg_fence();
            issue_pv(o, p, dv0 + vs * (kSlotBytes >> 4));
            wg_commit();
            pass_turn();
            wg_wait_release<1>(bar_empty + 8 * ks, lane);
            pin(s);
            softmax_tile<false>(s, m, l, a, 0, lane);
            pin(s);
            sched_fence(l[0] + l[1]);
            wg_wait_release<0>(bar_empty + 8 * vs, lane);
            pin(o);
            pin(p);
            if (__any_sync(0xffffffffu, a[0] != 1.f || a[1] != 1.f)) scale_rows(o, a[0], a[1]);
#pragma unroll
            for (int i = 0; i < 32; i++) p[i] = pack_bf16(s[2 * i], s[2 * i + 1]);
        }
        if (deep) {
            start_scores();
            pass_turn();
            mbar_wait(bar_empty + 8 * spare, spare_free);
            wg_wait<0>();
            pin(s);
            softmax_tile<false>(s, m, l, a_parked, 0, lane);
#pragma unroll
            for (int i = 0; i < 8; i++)
                asm volatile("st.shared.v4.u32 [%0], {%1, %2, %3, %4};"
                             ::"r"(stage + (i >> 2) * 16384 + (i & 3) * 512 + lane * 16),
                               "r"(pack_bf16(s[8 * i], s[8 * i + 1])), "r"(pack_bf16(s[8 * i + 2], s[8 * i + 3])),
                               "r"(pack_bf16(s[8 * i + 4], s[8 * i + 5])), "r"(pack_bf16(s[8 * i + 6], s[8 * i + 7])) : "memory");
        }
        a[0] = a[1] = 1.f;
        if (nt > 1) {
            start_scores();
            const uint32_t v_full = bar_full + 8 * r.slot, v_phase = r.phase, dv = dv0 + r.slot * (kSlotBytes >> 4);
            if (deep) r.next();
            const bool early = deep && wg_count(mbar_test(v_full, v_phase)) == 128;
            if (early) {
                wg_fence();
                issue_pv(o, p, dv);
                wg_commit();
                if (wg == 0) asm volatile("bar.arrive 6, 256;" ::: "memory");
                wg_wait<1>();
            } else {
                if (wg == 0) asm volatile("bar.arrive 6, 256;" ::: "memory");
                wg_wait<0>();
            }
            pin(s);
            pin(qf);
            softmax_tile<false>(s, m, l, a, 0, lane);
#pragma unroll
            for (int i = 0; i < 32; i++) qf[i] = pack_bf16(s[2 * i], s[2 * i + 1]);
            pin(qf);
            if (deep && !early) {
                mbar_wait(v_full, v_phase);
                wg_fence();
                issue_pv(o, p, dv);
                wg_commit();
            }
        } else {
#pragma unroll
            for (int i = 0; i < 32; i++) qf[i] = p[i];
        }

        l[0] += __shfl_xor_sync(0xffffffffu, l[0], 1);
        l[1] += __shfl_xor_sync(0xffffffffu, l[1], 1);
        l[0] += __shfl_xor_sync(0xffffffffu, l[0], 2);
        l[1] += __shfl_xor_sync(0xffffffffu, l[1], 2);
        const float inv0 = rcp(l[0]), inv1 = rcp(l[1]);
        const float fa0 = a[0] * inv0, fa1 = a[1] * inv1;
        const int mi = lane >> 3;
        uint32_t st_addr[4], ld_addr[2], fin_addr[2];
#pragma unroll
        for (int j = 0; j < 4; j++) st_addr[j] = stage + (lane & 15) * 128 + (((2 * j + (lane >> 4)) ^ (lane & 7)) << 4);
#pragma unroll
        for (int j = 0; j < 2; j++) ld_addr[j] = stage + 16384 + (4 * j + mi) * 128 + (((lane & 7) ^ (4 * j + mi)) << 4);
#pragma unroll
        for (int j = 0; j < 2; j++) fin_addr[j] = stage + 16384 + (lane & 7) * 128 + (((4 * j + mi) ^ (lane & 7)) << 4);
        uint4* dst = reinterpret_cast<uint4*>(out) + (size_t)(bh * kRows + warp * 16 + mi) * 16 + 8 + (lane & 7);
        pin(st_addr);
        pin(ld_addr);
        pin(fin_addr);
        asm volatile("" : "+l"(dst));
        const uint32_t dv_lo = dv0 + r.slot * (kSlotBytes >> 4);
        r.next();
        const uint32_t dv_hi = dv0 + r.slot * (kSlotBytes >> 4);
        sched_fence(inv0 + inv1);
        wg_wait<0>();
        pin(o);
        pin(p);
        if (deep) {
#pragma unroll
            for (int i = 0; i < 8; i++)
                asm volatile("ld.shared.v4.u32 {%0, %1, %2, %3}, [%4];"
                             : "=r"(p[4 * i]), "=r"(p[4 * i + 1]), "=r"(p[4 * i + 2]), "=r"(p[4 * i + 3])
                             : "r"(stage + (i >> 2) * 16384 + (i & 3) * 512 + lane * 16) : "memory");
        } else {
            mbar_wait(bar_empty + 8 * spare, spare_free);
        }
        float lo[32], hi[32], x[32], y[32];
#pragma unroll
        for (int i = 0; i < 32; i++) lo[i] = o[i] * a_parked[(i >> 1) & 1];
        pin(lo);
        pin(p);
        tail_units<0, 2>(lo, p, dv_lo, bar_tail);
#pragma unroll
        for (int i = 0; i < 32; i++) hi[i] = o[32 + i] * a_parked[(i >> 1) & 1];
        pin(hi);
        tail_units<2, 4>(lo, p, dv_lo, bar_tail);
        tail_units<0, 4, true>(x, qf, dv_lo + (16384 >> 4), bar_tail + 32);
        static_assert(kHeldUnits >= 1 && kHeldUnits <= 3, "the first unit of y is not held back");
        auto stage_half = [&](const float (&u)[32], const float (&v)[32], const int half) {
#pragma unroll
            for (int j = 0; j < 4; j++)
                stsm4(st_addr[j] + half * 16384,
                      pack_bf16(fmaf(v[8 * j], inv0, u[8 * j]), fmaf(v[8 * j + 1], inv0, u[8 * j + 1])),
                      pack_bf16(fmaf(v[8 * j + 2], inv1, u[8 * j + 2]), fmaf(v[8 * j + 3], inv1, u[8 * j + 3])),
                      pack_bf16(fmaf(v[8 * j + 4], inv0, u[8 * j + 4]), fmaf(v[8 * j + 5], inv0, u[8 * j + 5])),
                      pack_bf16(fmaf(v[8 * j + 6], inv1, u[8 * j + 6]), fmaf(v[8 * j + 7], inv1, u[8 * j + 7])));
        };
        wg_wait<4>();
        pin(lo);
#pragma unroll
        for (int i = 0; i < 32; i++) lo[i] *= (i & 2) ? fa1 : fa0;
        pin(lo);
        sched_fence(inv0);
        wg_wait<0>();
        pin(x);
        stage_half(lo, x, 0);
        asm volatile("fence.proxy.async.shared::cta;" ::: "memory");
        __syncwarp();
        if (lane == 0) mbar_arrive(bar_staged + 8 * wg);
        tail_units<0, 4>(hi, p, dv_hi, bar_tail + 64);
        tail_units<0, 4 - kHeldUnits, true>(y, qf, dv_hi + (16384 >> 4), bar_tail + 96);
        asm volatile("{ .reg .pred p; setp.ne.u32 p, %0, 0; @p bar.sync 8, 256; }" ::"r"(wg) : "memory");
        tail_units<4 - kHeldUnits, 4>(y, qf, dv_hi + (16384 >> 4), bar_tail + 96);
        asm volatile("{ .reg .pred p; setp.eq.u32 p, %0, 0; @p bar.arrive 8, 256; }" ::"r"(wg) : "memory");
        wg_wait<4>();
        pin(hi);
#pragma unroll
        for (int i = 0; i < 32; i++) hi[i] *= (i & 2) ? fa1 : fa0;
        pin(hi);
        sched_fence(inv0);
        wg_wait<0>();
        pin(y);
#pragma unroll
        for (int e = 0; e < 2; e++) {
            const float inv = e ? inv1 : inv0;
#pragma unroll
            for (int j = 0; j < 2; j++) {
                uint32_t wd[4];
#pragma unroll
                for (int k = 0; k < 4; k++) {
                    const int i = 16 * j + 4 * k + 2 * e;
                    wd[k] = pack_bf16(fmaf(y[i], inv, hi[i]), fmaf(y[i + 1], inv, hi[i + 1]));
                }
                stsm4(fin_addr[j] + e * 1024, wd[0], wd[1], wd[2], wd[3]);
            }
            __syncwarp();
#pragma unroll
            for (int i = 2 * e; i < 2 * e + 2; i++) {
                uint4 v;
                asm volatile("ld.shared.v4.u32 {%0, %1, %2, %3}, [%4];"
                             : "=r"(v.x), "=r"(v.y), "=r"(v.z), "=r"(v.w) : "r"(ld_addr[i & 1] + (i >> 1) * 1024) : "memory");
                asm volatile("st.global.v4.u32 [%0], {%1, %2, %3, %4};"
                             ::"l"(dst + i * 64), "r"(v.x), "r"(v.y), "r"(v.z), "r"(v.w) : "memory");
            }
        }
    }
}

typedef CUresult (*EncodeFn)(CUtensorMap*, CUtensorMapDataType, cuuint32_t, void*, const cuuint64_t*, const cuuint64_t*,
                             const cuuint32_t*, const cuuint32_t*, CUtensorMapInterleave, CUtensorMapSwizzle,
                             CUtensorMapL2promotion, CUtensorMapFloatOOBfill);

void encode_rows(EncodeFn enc, CUtensorMap* m, void* base, int box_rows) {
    cuuint64_t dims[2] = {(cuuint64_t)kD, (cuuint64_t)kGrid * kRows};
    cuuint64_t strides[1] = {(cuuint64_t)kD * 2};
    cuuint32_t box[2] = {64, (cuuint32_t)box_rows};
    cuuint32_t es[2] = {1, 1};
    enc(m, CU_TENSOR_MAP_DATA_TYPE_BFLOAT16, 2, base, dims, strides, box, es, CU_TENSOR_MAP_INTERLEAVE_NONE,
        CU_TENSOR_MAP_SWIZZLE_128B, CU_TENSOR_MAP_L2_PROMOTION_L2_128B, CU_TENSOR_MAP_FLOAT_OOB_FILL_NONE);
}

void encode_cache(EncodeFn enc, CUtensorMap* m, void* base, int num_phys, int rows, int halves, int groups) {
    cuuint64_t dims[5] = {64, 8, 2, (cuuint64_t)num_phys * 2, (cuuint64_t)kHkv};
    cuuint64_t strides[4] = {(cuuint64_t)kHkv * kD * 2, 128, (cuuint64_t)8 * kHkv * kD * 2, (cuuint64_t)kD * 2};
    cuuint32_t box[5] = {64, (cuuint32_t)rows, (cuuint32_t)halves, (cuuint32_t)groups, 1};
    cuuint32_t es[5] = {1, 1, 1, 1, 1};
    enc(m, CU_TENSOR_MAP_DATA_TYPE_BFLOAT16, 5, base, dims, strides, box, es, CU_TENSOR_MAP_INTERLEAVE_NONE,
        CU_TENSOR_MAP_SWIZZLE_128B, CU_TENSOR_MAP_L2_PROMOTION_L2_128B, CU_TENSOR_MAP_FLOAT_OOB_FILL_NONE);
}

void encode_window(EncodeFn enc, CUtensorMap* m, void* base, int num_phys) {
    const cuuint64_t token = (cuuint64_t)kHkv * kD * 2;
    cuuint64_t dims[5] = {64, 8, 2, (cuuint64_t)num_phys * kPage - 7, (cuuint64_t)kHkv};
    cuuint64_t strides[4] = {token, 128, token, (cuuint64_t)kD * 2};
    cuuint32_t box[5] = {64, 8, 2, 1, 1};
    cuuint32_t es[5] = {1, 1, 1, 1, 1};
    enc(m, CU_TENSOR_MAP_DATA_TYPE_BFLOAT16, 5, base, dims, strides, box, es, CU_TENSOR_MAP_INTERLEAVE_NONE,
        CU_TENSOR_MAP_SWIZZLE_128B, CU_TENSOR_MAP_L2_PROMOTION_L2_128B, CU_TENSOR_MAP_FLOAT_OOB_FILL_NONE);
}

}

extern "C" void kernel_launch(void* const* d_in, const int* in_sizes, int n_in, void* d_out, int out_size) {
    (void)n_in;
    (void)out_size;
    void* fn = nullptr;
    cudaDriverEntryPointQueryResult qr;
    cudaGetDriverEntryPoint("cuTensorMapEncodeTiled", &fn, cudaEnableDefault, &qr);
    EncodeFn enc = (EncodeFn)fn;
    const int num_phys = in_sizes[1] / (kPage * kHkv * kD);
    CUtensorMap mq, mk, mv, mvh, mo, mkp, mvp;
    encode_rows(enc, &mq, d_in[0], kRows);
    encode_rows(enc, &mo, d_out, 64);
    encode_cache(enc, &mk, d_in[1], num_phys, 8, 2, 2);
    encode_cache(enc, &mv, d_in[2], num_phys, 8, 2, 2);
    encode_cache(enc, &mvh, d_in[2], num_phys, 8, 1, 2);
    encode_window(enc, &mkp, d_in[1], num_phys);
    encode_window(enc, &mvp, d_in[2], num_phys);
    cudaFuncSetAttribute(paged_attn_kernel, cudaFuncAttributeMaxDynamicSharedMemorySize, kSmemBytes);
    paged_attn_kernel<<<kGrid, kThreads, kSmemBytes>>>((const __nv_bfloat16*)d_in[0], (const int*)d_in[3], (const int*)d_in[4],
                                                       (__nv_bfloat16*)d_out, num_phys, mq, mk, mv, mvh, mo, mkp, mvp);
}
```
